```python
import torch

def _softmax(x, axis=-1):
    return torch.softmax(x, dim=axis)

def _gelu(x):
    return torch.nn.functional.gelu(x, approximate='tanh')

def _silu(x):
    return torch.nn.functional.silu(x)

def _sigmoid(x):
    return torch.sigmoid(x)

def _layernorm(x, axis=-1, eps=1e-05):
    m = x.mean(dim=axis, keepdim=True)
    v = x.var(dim=axis, keepdim=True, unbiased=False)
    return (x - m) / torch.sqrt(v + eps)

def _scatter_add(tgt, idx, src, axis=0):
    return tgt.clone().index_add_(axis, idx, src)

def _segment_sum(src, seg, n):
    out = torch.zeros((n,) + src.shape[1:], dtype=src.dtype)
    return out.index_add_(0, seg, src)

def _pad(x, pw):
    flat = tuple((v for pair in reversed(pw) for v in pair))
    return torch.nn.functional.pad(x, flat)
kernel_name = 'adaLN_cond__mha_block_cached__dense_activation_relu__decode'

def setup_inputs():

    _w = lambda a: (lambda t: t.to(torch.bfloat16) if t.is_floating_point() else t)(torch.as_tensor(a))

    def _A_setup():
        B, Sq, D = (2, 1, 576)
        H, Sk, Dh = (32, 16384, 128)
        return {'x': _w((lambda *s: torch.randn(*s, dtype=torch.bfloat16) * 0.1)(B, Sq, D)), 'k_cache': _w((lambda *s: torch.randn(*s, dtype=torch.bfloat16) * 0.8)(B, H, Sk, Dh)), 'v_cache': _w((lambda *s: torch.randn(*s, dtype=torch.bfloat16) * 1.6)(B, H, Sk, Dh)), 'wq': _w((lambda *s: torch.randn(*s, dtype=torch.bfloat16) * 0.8)(D, H * Dh) * D ** (-0.5)), 'wo': _w((lambda *s: torch.randn(*s, dtype=torch.bfloat16) * 1.6)(H * Dh, D) * (H * Dh) ** (-0.5))}
    _A_in = _A_setup()

    def _B_setup():
        B, S, D, Dff = (2, 1, 576, 4608)
        return {'x': _w((lambda *s: torch.randn(*s, dtype=torch.bfloat16) * 0.1)(B, S, D)), 'w1': _w((lambda *s: torch.randn(*s, dtype=torch.bfloat16) * 0.1)(D, Dff)), 'w2': _w((lambda *s: torch.randn(*s, dtype=torch.bfloat16) * 0.1)(Dff, D))}
    _B_in = _B_setup()
    return {'A_x': _A_in['x'], 'A_k_cache': _A_in['k_cache'], 'A_v_cache': _A_in['v_cache'], 'A_wq': _A_in['wq'], 'A_wo': _A_in['wo'], 'B_x': _B_in['x'], 'B_w1': _B_in['w1'], 'B_w2': _B_in['w2'], 'c': _w((lambda *s: torch.randn(*s, dtype=torch.bfloat16) * 0.2)(2, 576) * 8.0), 'w_mod': _w((lambda *s: torch.randn(*s, dtype=torch.bfloat16) * 0.2)(576, 6 * 576) * 576 ** (-0.5) * 8.0)}

def reference(A_x, A_k_cache, A_v_cache, A_wq, A_wo, B_x, B_w1, B_w2, c, w_mod):

    def _A_ref(x, k_cache, v_cache, wq, wo):
        B, Sq, D = x.shape
        H, Dh = (32, 128)
        q = (lambda x, *d: x.permute(*d))((x @ wq).reshape(B, Sq, H, Dh), 0, 2, 1, 3)
        scores = torch.einsum('bhqd,bhkd->bhqk', q, k_cache) * Dh ** (-0.5)
        p = _softmax(scores, axis=-1)
        o = torch.einsum('bhqk,bhkd->bhqd', p, v_cache)
        return (lambda x, *d: x.permute(*d))(o, 0, 2, 1, 3).reshape(B, Sq, H * Dh) @ wo

    def _B_ref(x, w1, w2):
        h = torch.einsum('bsd,df->bsf', x, w1)
        zero = torch.zeros_like(h)
        h = torch.maximum(h, zero)
        return torch.einsum('bsf,fd->bsd', h, w2)
    x = A_x
    mod = (_silu(c) @ w_mod).reshape(c.shape[0], 6, 1, -1)
    sa, ca, ga, sb, cb, gb = (mod[:, 0].clone(), mod[:, 1].clone(), mod[:, 2].clone(), mod[:, 3].clone(), mod[:, 4].clone(), mod[:, 5].clone())
    h = _layernorm(x, axis=-1) * (1 + ca) + sa
    x = x + ga * _A_ref(h, A_k_cache, A_v_cache, A_wq, A_wo)
    h = _layernorm(x, axis=-1) * (1 + cb) + sb
    x = x + gb * _B_ref(h, B_w1, B_w2)
    return x
```

```cpp
#include <cuda_runtime.h>
#include <cuda_bf16.h>
#include <cuda.h>
#include <stdint.h>

namespace {

typedef __nv_bfloat16 bf16;

constexpr int D_MODEL = 576;
constexpr int NHEAD   = 32;
constexpr int DHEAD   = 128;
constexpr int SKV     = 16384;
constexpr int DFF     = 4608;
constexpr int NMODC   = 6 * D_MODEL;

constexpr int NCTA  = 132;
constexpr int NATT  = 128;
constexpr int NMLP  = 96;
constexpr int OWN0  = 96;
constexpr int NOWN  = 36;
constexpr int NTHR  = 352;
constexpr int NWORK = 288;

constexpr int TILE_KEYS  = 64;
constexpr int TILE_BYTES = TILE_KEYS * DHEAD * 2;
constexpr int NSLOT      = 13;
constexpr int NPAIR      = (SKV / 2) / TILE_KEYS;
constexpr int NTILE      = 2 * NPAIR;
constexpr int SLOT_ROT   = 4;
#define WIN 4
#define WIN0 2
#define WINW 3
#define SCHED 0x7f80
#define SCHED2 0x0180
#define FB_GAIN 128
#define FB_MIN 3
#define FB_MAX 6
#define X2_REP 1
#define MOD_REP 1
constexpr int SCHED_K0 = 249;

constexpr int SM_RING  = 0;
constexpr int SM_WO    = 0;
constexpr int WO_BOX   = 128 * 144;
constexpr int SM_W1    = SM_WO + 2 * WO_BOX;
constexpr int W1_BOX   = 192 * 96;
constexpr int SM_W2    = SM_W1 + 3 * W1_BOX;
constexpr int W2_BOX   = 48 * 144;
constexpr int SM_WEND  = SM_W2 + 8 * W2_BOX;
constexpr int SM_HP    = SM_WEND;
constexpr int P_BOX    = 192 * 64;
constexpr int SM_PM0   = 12 * TILE_BYTES;
constexpr int SM_PQ    = 4 * TILE_BYTES - 3 * P_BOX;
constexpr int XP_COL   = 144;
constexpr int XP_WARP  = 4 * XP_COL;
constexpr int SM_XPD   = NSLOT * TILE_BYTES;
constexpr int SM_XPC   = SM_XPD + 9 * XP_WARP;
constexpr int SM_RED   = SM_XPC + 9 * XP_WARP;
constexpr int SM_ML    = SM_RED + 4608;
constexpr int SM_Q     = SM_ML + 256;
constexpr int SM_O     = SM_Q + 256;
constexpr int SM_H1    = SM_O + 640;
constexpr int SM_X2O   = SM_H1 + 192;
constexpr int SM_BAR   = SM_X2O + 128;
constexpr int NBAR     = 2 * NSLOT + 8 + 5;
constexpr int SM_TOTAL = SM_BAR + 8 * NBAR;
static_assert(SM_WEND == 9 * TILE_BYTES, "layout");
static_assert(SM_PQ >= 2 * P_BOX && SM_PQ % 512 == 0, "layout");
static_assert(SM_TOTAL <= 232448, "smem");
static_assert((NTILE - NSLOT + SLOT_ROT) % NSLOT == 0, "tile NTILE-13 must sit at ring position 0");

constexpr int PART_STRIDE = 160;

struct Scratch {
    uint32_t epoch[32];
    uint32_t prog[4 * 32];
    uint32_t mod[NMODC * 2];
    uint32_t sc[MOD_REP * D_MODEL * 4];
    uint32_t q[2 * NHEAD * DHEAD];
    uint32_t part[NATT * PART_STRIDE];
    uint32_t y[NOWN * NHEAD * 32];
    uint32_t x2[X2_REP * D_MODEL * 2];
    uint32_t z[NOWN * NMLP * 32];
};
__device__ __align__(128) Scratch g_scratch;

#define CSTAMP(i) do {} while (0)
#define STAMP(i) do {} while (0)
#define STAMP1(i) do {} while (0)

constexpr int SPIN_LIMIT = 1 << 22;

__device__ __forceinline__ uint32_t smem_u32(const void* p) { return (uint32_t)__cvta_generic_to_shared(p); }

__device__ __forceinline__ void mbar_init(uint32_t a, uint32_t cnt) {
    asm volatile("mbarrier.init.shared::cta.b64 [%0], %1;" ::"r"(a), "r"(cnt) : "memory");
}
__device__ __forceinline__ void mbar_expect(uint32_t a, uint32_t bytes) {
    asm volatile("mbarrier.arrive.expect_tx.shared::cta.b64 _, [%0], %1;" ::"r"(a), "r"(bytes) : "memory");
}
__device__ __forceinline__ void mbar_arrive(uint32_t a) {
    asm volatile("mbarrier.arrive.shared::cta.b64 _, [%0];" ::"r"(a) : "memory");
}
__device__ __forceinline__ uint32_t mbar_test(uint32_t a, uint32_t parity) {
    uint32_t ok;
    asm volatile("{.reg .pred p; mbarrier.test_wait.parity.shared::cta.b64 p, [%1], %2; selp.u32 %0, 1, 0, p;}"
                 : "=r"(ok) : "r"(a), "r"(parity) : "memory");
    return ok;
}
__device__ __forceinline__ void mbar_wait(uint32_t a, uint32_t parity) {
    int it = 0;
    while (true) {
        uint32_t ok;
        asm volatile("{.reg .pred p; mbarrier.try_wait.parity.shared::cta.b64 p, [%1], %2; selp.u32 %0, 1, 0, p;}"
                     : "=r"(ok) : "r"(a), "r"(parity) : "memory");
        if (ok) break;
        if (++it > SPIN_LIMIT) __trap();
    }
}
__device__ __forceinline__ void bulk_load(uint32_t dst, const void* src, uint32_t bytes, uint32_t bar, uint64_t pol) {
    asm volatile("cp.async.bulk.shared::cluster.global.mbarrier::complete_tx::bytes.L2::cache_hint [%0], [%1], %2, [%3], %4;"
                 ::"r"(dst), "l"(src), "r"(bytes), "r"(bar), "l"(pol) : "memory");
}
__device__ __forceinline__ void tensor_load(uint32_t dst, const CUtensorMap* map, int c0, int c1, uint32_t bar) {
    asm volatile("cp.async.bulk.tensor.2d.shared::cluster.global.mbarrier::complete_tx::bytes [%0], [%1, {%3, %4}], [%2];"
                 ::"r"(dst), "l"(map), "r"(bar), "r"(c0), "r"(c1) : "memory");
}
template <int ID, int N>
__device__ __forceinline__ void bar_sync() { asm volatile("bar.sync %0, %1;" ::"n"(ID), "n"(N) : "memory"); }
template <int ID, int N>
__device__ __forceinline__ void bar_arrive() { asm volatile("bar.arrive %0, %1;" ::"n"(ID), "n"(N) : "memory"); }

__device__ __forceinline__ void ldsm4(uint32_t (&r)[4], uint32_t addr) {
    asm volatile("ldmatrix.sync.aligned.m8n8.x4.shared.b16 {%0,%1,%2,%3}, [%4];"
                 : "=r"(r[0]), "=r"(r[1]), "=r"(r[2]), "=r"(r[3]) : "r"(addr) : "memory");
}
__device__ __forceinline__ void ldsm4t(uint32_t (&r)[4], uint32_t addr) {
    asm volatile("ldmatrix.sync.aligned.m8n8.x4.trans.shared.b16 {%0,%1,%2,%3}, [%4];"
                 : "=r"(r[0]), "=r"(r[1]), "=r"(r[2]), "=r"(r[3]) : "r"(addr) : "memory");
}
__device__ __forceinline__ void mma16816(float (&d)[4], const uint32_t (&a)[4], uint32_t b0, uint32_t b1) {
    asm volatile("mma.sync.aligned.m16n8k16.row.col.f32.bf16.bf16.f32 {%0,%1,%2,%3}, {%4,%5,%6,%7}, {%8,%9}, {%0,%1,%2,%3};"
                 : "+f"(d[0]), "+f"(d[1]), "+f"(d[2]), "+f"(d[3])
                 : "r"(a[0]), "r"(a[1]), "r"(a[2]), "r"(a[3]), "r"(b0), "r"(b1));
}

__device__ __forceinline__ uint4 ld_rlx4(const uint32_t* p) {
    uint4 v;
    asm volatile("ld.relaxed.gpu.global.v4.u32 {%0,%1,%2,%3}, [%4];" : "=r"(v.x), "=r"(v.y), "=r"(v.z), "=r"(v.w) : "l"(p) : "memory");
    return v;
}
__device__ __forceinline__ uint2 ld_rlx2(const uint32_t* p) {
    uint2 v;
    asm volatile("ld.relaxed.gpu.global.v2.u32 {%0,%1}, [%2];" : "=r"(v.x), "=r"(v.y) : "l"(p) : "memory");
    return v;
}
__device__ __forceinline__ uint32_t ld_rlx1(const uint32_t* p) {
    uint32_t v;
    asm volatile("ld.relaxed.gpu.global.u32 %0, [%1];" : "=r"(v) : "l"(p) : "memory");
    return v;
}
__device__ __forceinline__ void st_rlx4(uint32_t* p, uint32_t a, uint32_t b, uint32_t c, uint32_t d) {
    asm volatile("st.relaxed.gpu.global.v4.u32 [%0], {%1,%2,%3,%4};" ::"l"(p), "r"(a), "r"(b), "r"(c), "r"(d) : "memory");
}
__device__ __forceinline__ void st_rlx2(uint32_t* p, uint32_t a, uint32_t b) {
    asm volatile("st.relaxed.gpu.global.v2.u32 [%0], {%1,%2};" ::"l"(p), "r"(a), "r"(b) : "memory");
}
__device__ __forceinline__ void st_rlx1(uint32_t* p, uint32_t a) {
    asm volatile("st.relaxed.gpu.global.u32 [%0], %1;" ::"l"(p), "r"(a) : "memory");
}
__device__ __forceinline__ uint32_t enc(float v, uint32_t tag) { return (__float_as_uint(v) & ~3u) | tag; }
__device__ __forceinline__ float dec(uint32_t w) { return __uint_as_float(w & ~3u); }
__device__ __forceinline__ uint32_t bad4(const uint4& v, uint32_t tag) { return (v.x ^ tag) | (v.y ^ tag) | (v.z ^ tag) | (v.w ^ tag); }
template <int N>
__device__ __forceinline__ void poll4(uint4 (&v)[N], const uint32_t* p, int stride, uint32_t tag) {
    int it = 0;
    while (true) {
        uint32_t bad = 0;
#pragma unroll
        for (int i = 0; i < N; i++) v[i] = ld_rlx4(p + i * stride);
#pragma unroll
        for (int i = 0; i < N; i++) bad |= bad4(v[i], tag);
        if (__all_sync(0xffffffffu, (bad & 3u) == 0)) break;
        if (++it > SPIN_LIMIT) __trap();
    }
}

__device__ __forceinline__ float rbf(float v) {
    uint32_t r;
    asm("cvt.rn.bf16x2.f32 %0, %1, %2;" : "=r"(r) : "f"(v), "f"(0.0f));
    return __uint_as_float(r);
}
__device__ __forceinline__ float bflo(uint32_t w) { return __uint_as_float(w << 16); }
__device__ __forceinline__ float bfhi(uint32_t w) { return __uint_as_float(w & 0xffff0000u); }
__device__ __forceinline__ uint32_t pack_bf(float lo, float hi) {
    uint32_t r;
    asm("cvt.rn.bf16x2.f32 %0, %1, %2;" : "=r"(r) : "f"(hi), "f"(lo));
    return r;
}
__device__ __forceinline__ float ex2(float x) {
    float r;
    asm("ex2.approx.ftz.f32 %0, %1;" : "=f"(r) : "f"(x));
    return r;
}
__device__ __forceinline__ float rcp(float x) {
    float r;
    asm("rcp.approx.ftz.f32 %0, %1;" : "=f"(r) : "f"(x));
    return r;
}
__device__ __forceinline__ uint32_t ldg32(const void* p) {
    uint32_t v;
    asm volatile("ld.global.nc.u32 %0, [%1];" : "=r"(v) : "l"(p));
    return v;
}
__device__ __forceinline__ float silu_bf(float v) { return __fdividef(v, 1.0f + __expf(-v)); }

__device__ __forceinline__ void ln_partial(float a0, float a1, float b0, float b1, float* ml, int warp, int lane) {
    const bool odd = lane & 1;
    const float s0 = a0 + a1, q0 = fmaf(a0, a0, a1 * a1), s1 = b0 + b1, q1 = fmaf(b0, b0, b1 * b1);
    float s = (odd ? s1 : s0) + __shfl_xor_sync(0xffffffffu, odd ? s0 : s1, 1);
    float q = (odd ? q1 : q0) + __shfl_xor_sync(0xffffffffu, odd ? q0 : q1, 1);
#pragma unroll
    for (int o = 2; o < 32; o <<= 1) {
        s += __shfl_xor_sync(0xffffffffu, s, o);
        q += __shfl_xor_sync(0xffffffffu, q, o);
    }
    if (lane < 2) *reinterpret_cast<float2*>(ml + 4 * warp + 2 * lane) = make_float2(s, q);
}
__device__ __forceinline__ void ln_stats(const float* ml, float& m0, float& r0, float& m1, float& r1) {
    float4 t[9];
#pragma unroll
    for (int i = 0; i < 9; i++) t[i] = *reinterpret_cast<const float4*>(ml + 4 * i);
#pragma unroll
    for (int o = 1; o < 9; o <<= 1)
#pragma unroll
        for (int i = 0; i + o < 9; i += 2 * o) { t[i].x += t[i + o].x; t[i].y += t[i + o].y; t[i].z += t[i + o].z; t[i].w += t[i + o].w; }
    m0 = t[0].x * (1.0f / D_MODEL);
    m1 = t[0].z * (1.0f / D_MODEL);
    r0 = rsqrtf(fmaxf(fmaf(-m0, m0, t[0].y * (1.0f / D_MODEL)), 0.0f) + 1e-5f);
    r1 = rsqrtf(fmaxf(fmaf(-m1, m1, t[0].w * (1.0f / D_MODEL)), 0.0f) + 1e-5f);
}

__device__ __forceinline__ void gemv32(uint32_t box, const uint4& f0, const uint4& f1, float* red, int warp, int lane) {
    const uint32_t a0 = box + ((warp % 3) * 64 + (lane & 7) + (lane >> 4) * 8) * 64 + ((((lane >> 3) & 1) ^ ((lane & 7) >> 1)) << 4);
    const uint32_t bf[8] = {f0.x, f0.y, f0.z, f0.w, f1.x, f1.y, f1.z, f1.w};
    float d[2][4] = {{0.f, 0.f, 0.f, 0.f}, {0.f, 0.f, 0.f, 0.f}};
#pragma unroll
    for (int s = 0; s < 4; s++)
#pragma unroll
        for (int t = 0; t < 2; t++) {
            uint32_t a[4];
            ldsm4t(a, (a0 + s * 1024) ^ (t << 5));
            mma16816(d[t], a, bf[2 * s], bf[2 * s + 1]);
        }
    if ((lane & 3) == 0) {
#pragma unroll
        for (int t = 0; t < 2; t++) {
            *reinterpret_cast<float2*>(red + warp * 64 + (16 * t + (lane >> 2)) * 2) = make_float2(d[t][0], d[t][1]);
            *reinterpret_cast<float2*>(red + warp * 64 + (16 * t + 8 + (lane >> 2)) * 2) = make_float2(d[t][2], d[t][3]);
        }
    }
}
__device__ __forceinline__ float sum9(const float* p, int stride) {
    float v[9];
#pragma unroll
    for (int i = 0; i < 9; i++) v[i] = p[i * stride];
    return ((v[0] + v[1]) + (v[2] + v[3])) + ((v[4] + v[5]) + (v[6] + v[7])) + v[8];
}

__device__ __forceinline__ uint32_t ring_pos(int slot) { return (slot + SLOT_ROT >= NSLOT ? slot + SLOT_ROT - NSLOT : slot + SLOT_ROT) * TILE_BYTES; }

__global__ void __launch_bounds__(NTHR, 1)
adaln_block_kernel(const __grid_constant__ CUtensorMap map_wm, const __grid_constant__ CUtensorMap map_wq,
                   const __grid_constant__ CUtensorMap map_wo, const __grid_constant__ CUtensorMap map_w1,
                   const __grid_constant__ CUtensorMap map_w2, const bf16* __restrict__ x, const bf16* __restrict__ kc,
                   const bf16* __restrict__ vc, const bf16* __restrict__ cnd, bf16* __restrict__ out, Scratch* S) {
    extern __shared__ __align__(1024) unsigned char smem[];
    uint32_t sbase = smem_u32(smem);
    asm volatile("" : "+r"(sbase));
    const int tid = threadIdx.x, warp = tid >> 5, lane = tid & 31;
    const int g = lane >> 2, c4 = lane & 3;
    const int cta = blockIdx.x;
    const bool is_att = cta < NATT, is_mlp = cta < NMLP, is_own = cta >= OWN0;
    const int head = cta >> 2, qq = cta & 3, bat = (cta >> 1) & 1, half = cta & 1;
    const int own = cta - OWN0;

    const uint32_t bar_full = sbase + SM_BAR, bar_empty = bar_full + 8 * NSLOT, bar_w = bar_empty + 8 * NSLOT;
    const uint32_t bar_near = bar_w + 64, bar_fm = bar_near + 8, bar_fq = bar_fm + 8, bar_pm = bar_fq + 8, bar_pq = bar_pm + 8;
    float* s_red = reinterpret_cast<float*>(smem + SM_RED);
    float* s_ml = reinterpret_cast<float*>(smem + SM_ML);

    STAMP(0); CSTAMP(30);

    if (warp == 10) {
        if (lane == 0) {
            mbar_init(bar_pm, 1);
            mbar_init(bar_pq, 1);
            asm volatile("fence.mbarrier_init.release.cluster;" ::: "memory");
            STAMP1(23);
            if (is_own) {
                mbar_expect(bar_pm, 3 * P_BOX);
#pragma unroll
                for (int i = 0; i < 3; i++) tensor_load(sbase + (i == 0 ? SM_PM0 : (i - 1) * P_BOX), &map_wm, own * 32, i * 192, bar_pm);
            }
            if (is_att) {
                mbar_expect(bar_pq, 3 * P_BOX);
#pragma unroll
                for (int i = 0; i < 3; i++) tensor_load(sbase + SM_PQ + i * P_BOX, &map_wq, cta * 32, i * 192, bar_pq);
            }
        }
        __syncwarp();
        STAMP(29);
        bar_sync<1, NTHR>();
        if (lane != 0) return;
        if (!is_att) {
#pragma unroll 1
            for (int u = 0; u < 18; u++) {
                mbar_wait(bar_fm, u & 1);
                mbar_expect(bar_pm, 3 * P_BOX);
#pragma unroll
                for (int i = 0; i < 3; i++)
                    tensor_load(sbase + (i == 0 ? SM_PM0 : (i - 1) * P_BOX), &map_wm, ((2 + cta - NATT) * 18 + u) * 32, i * 192, bar_pm);
            }
            return;
        }
        uint64_t pol;
        asm volatile("createpolicy.fractional.L2::evict_first.b64 %0, 1.0;" : "=l"(pol));
        const size_t base = ((size_t)(bat * NHEAD + head) * SKV + (size_t)half * (SKV / 2)) * DHEAD * 2;
        const char* ksrc = reinterpret_cast<const char*>(kc) + base;
        const char* vsrc = reinterpret_cast<const char*>(vc) + base;
        const uint32_t sched = is_mlp ? SCHED : SCHED2;
        const int nitem = NTILE + (is_mlp ? 8 : 2);
        int ti = 0, slot = 0, ui = 0, freed = NTILE - NSLOT, fslot = (NTILE - NSLOT) % NSLOT;
        int landed = 0, wslot = 0, wui = 0, win = WIN;
        uint32_t ph = 1, wph = 0, fph = ((NTILE - NSLOT) / NSLOT) & 1, wdst = 0;
        uint32_t* prog = S->prog;
        int total = 0, mine = 0;
#pragma unroll 1
        for (int k = 0; k < nitem; k++) {
            while (landed + win <= k) {
                const bool u = landed >= SCHED_K0 && ((sched >> (landed - SCHED_K0)) & 1);
                mbar_wait(u ? bar_w + 8 * wui : bar_full + 8 * wslot, u ? 0u : wph);
                if (u) wui++;
                else if (++wslot == NSLOT) { wslot = 0; wph ^= 1; }
                landed++;
            }
            if (k >= SCHED_K0 && ((sched >> (k - SCHED_K0)) & 1)) {
                const int needf = NTILE - NSLOT + (ui < 6 ? ui + 2 : 9);
                while (freed < needf) {
                    mbar_wait(bar_empty + 8 * fslot, fph);
                    if (++fslot == NSLOT) { fslot = 0; fph ^= 1; }
                    freed++;
                }
                const CUtensorMap* map = ui < 2 ? &map_wo : (ui < 5 ? &map_w1 : &map_w2);
                const int nb = ui < 5 ? 1 : (ui < 7 ? 3 : 2), bytes = ui < 5 ? WO_BOX : W2_BOX;
                int c0 = ui < 2 ? qq * 144 + ui * 72 : (ui < 5 ? cta * 48 : (ui - 5) * 216);
                const int c1 = ui < 2 ? head * 128 : (ui < 5 ? (ui - 2) * 192 : cta * 48);
                mbar_expect(bar_w + 8 * ui, nb * bytes);
#pragma unroll 1
                for (int i = 0; i < nb; i++) {
                    tensor_load(sbase + wdst, map, c0, c1, bar_w + 8 * ui);
                    wdst += bytes;
                    c0 += 72;
                }
                ui++;
            } else {
                if (ti >= NSLOT) mbar_wait(bar_empty + 8 * slot, ph);
                else {
                    if (ti == WIN0) { if (!is_own) STAMP1(9); mbar_wait(bar_pq, 0); if (!is_own) STAMP1(24); else STAMP1(14); }
                    if (ti == 8 && is_own) mbar_wait(bar_fm, 0);
                    if (ti == 10) {
                        asm volatile("prefetch.tensormap [%0];" ::"l"(&map_wo) : "memory");
                        asm volatile("prefetch.tensormap [%0];" ::"l"(&map_w1) : "memory");
                        asm volatile("prefetch.tensormap [%0];" ::"l"(&map_w2) : "memory");
                        prog += ((ld_rlx1(S->epoch) + 1) & 1) * 32;
                        STAMP1(21);
                        mbar_wait(bar_fq, 0);
                    }
                }
                mbar_expect(bar_full + 8 * slot, TILE_BYTES);
                bulk_load(sbase + SM_RING + ring_pos(slot), ((ti & 1) ? vsrc : ksrc) + (size_t)(ti >> 1) * TILE_BYTES, TILE_BYTES,
                          bar_full + 8 * slot, pol);
                if (++slot == NSLOT) { slot = 0; ph ^= 1; }
                ti++;
                if ((ti & 3) == 0 && ti >= 16) {
                    const int w = WIN + (total - mine * NATT + (NATT / 2 + 1 + NATT * 8 + FB_GAIN / 2)) / FB_GAIN - NATT * 8 / FB_GAIN;
                    if (mine) win = min(max(w, FB_MIN), FB_MAX);
                    mine++;
                    asm volatile("atom.relaxed.gpu.global.add.u32 %0, [%1], 1;" : "=r"(total) : "l"(prog) : "memory");
                }
                if (ti == NTILE - 3) mbar_arrive(bar_near);
                if (ti == NTILE) win = WINW;
            }
        }
        return;
    }

    uint32_t epoch = ld_rlx1(S->epoch);
    uint32_t x0 = 0, x1 = 0, c0 = 0, c1 = 0;
    if (warp < 9) {
        x0 = ldg32(x + 2 * tid);
        x1 = ldg32(x + D_MODEL + 2 * tid);
        if (is_own) { c0 = ldg32(cnd + 2 * tid); c1 = ldg32(cnd + D_MODEL + 2 * tid); }
    }
    if (lane == 0) {
#pragma unroll 1
        for (int i = warp; i < NBAR - 2; i += 10) mbar_init(bar_full + 8 * i, (i >= NSLOT && i < 2 * NSLOT) ? 4 : 1);
        asm volatile("fence.mbarrier_init.release.cluster;" ::: "memory");
    }
    __syncwarp();
    STAMP(15);
    bar_sync<1, NTHR>();
    asm volatile("" : "+r"(epoch), "+r"(x0), "+r"(x1), "+r"(c0), "+r"(c1));
    epoch += 1;
    const uint32_t tag = epoch & 3u;

    if (warp == 9) {
        if (is_att) {
            uint4 v[1];
            poll4<1>(v, S->q + bat * (NHEAD * DHEAD) + head * DHEAD + lane * 4, 0, tag);
            *reinterpret_cast<uint2*>(smem + SM_Q + lane * 8) =
                make_uint2(__byte_perm(v[0].x, v[0].y, 0x7632), __byte_perm(v[0].z, v[0].w, 0x7632));
            __syncwarp();
            bar_arrive<5, 288>();
        }
        uint4 ga4 = make_uint4(0, 0, 0, 0);
        uint32_t xo0 = 0, xo1 = 0;
        float gb1 = 0.f;
        const int nr = is_own ? 1 : 9;
#pragma unroll 1
        for (int r = 0; r < nr; r++) {
            const int pr = lane + 32 * r;
            const uint32_t* pa = is_own ? S->mod + (2 * D_MODEL + own * 16 + 2 * (lane & 7)) * 2 : S->mod + (3 * D_MODEL + 2 * pr) * 2;
            const uint32_t* pb = is_own ? S->mod + (5 * D_MODEL + own * 16 + 2 * g) * 2 : S->mod + (4 * D_MODEL + 2 * pr) * 2;
            uint4 sb, cb;
            int it = 0;
            while (true) {
                sb = ld_rlx4(pa);
                cb = ld_rlx4(pb);
                if (__all_sync(0xffffffffu, ((bad4(sb, tag) | bad4(cb, tag)) & 3u) == 0)) break;
                if (++it > SPIN_LIMIT) __trap();
                __nanosleep(2000);
            }
            if (is_own) {
                ga4 = sb;
                gb1 = dec(c4 == 0 ? cb.x : (c4 == 1 ? cb.y : (c4 == 2 ? cb.z : cb.w)));
                xo0 = ldg32(x + own * 16 + 2 * (lane & 7));
                xo1 = ldg32(x + D_MODEL + own * 16 + 2 * (lane & 7));
            } else {
                unsigned char* p = smem + SM_XPC + r * XP_WARP + (c4 * 8 + g) * 4;
                *reinterpret_cast<uint32_t*>(p) = pack_bf(1.0f + dec(cb.x), 1.0f + dec(cb.z));
                *reinterpret_cast<uint32_t*>(p + XP_COL) = pack_bf(1.0f + dec(cb.y), 1.0f + dec(cb.w));
                *reinterpret_cast<uint32_t*>(p + 2 * XP_COL) = __byte_perm(sb.x, sb.z, 0x7632);
                *reinterpret_cast<uint32_t*>(p + 3 * XP_COL) = __byte_perm(sb.y, sb.w, 0x7632);
            }
        }
        if (is_att) {
            mbar_wait(bar_near, 0);
            const uint32_t* pp = S->part + head * 4 * PART_STRIDE;
            uint2 t;
            int it = 0;
            while (true) {
                t = ld_rlx2(pp + c4 * PART_STRIDE + 128);
                if (__all_sync(0xffffffffu, (((t.x ^ tag) | (t.y ^ tag)) & 3u) == 0)) break;
                if (++it > SPIN_LIMIT) __trap();
            }
            const float mo = __shfl_xor_sync(0xffffffffu, dec(t.x), 1);
            float e = ex2(dec(t.x) - fmaxf(dec(t.x), mo));
            const float le = e * dec(t.y);
            e *= rcp(le + __shfl_xor_sync(0xffffffffu, le, 1));
            const float e0 = __shfl_sync(0xffffffffu, e, 0), e1 = __shfl_sync(0xffffffffu, e, 1);
            const float e2 = __shfl_sync(0xffffffffu, e, 2), e3 = __shfl_sync(0xffffffffu, e, 3);
            uint4 u[4];
            poll4<4>(u, pp + 4 * lane, PART_STRIDE, tag);
            STAMP(25);
            uint32_t* so = reinterpret_cast<uint32_t*>(smem + SM_O) + (c4 & 1) * 40 + g * 2 + (c4 >> 1);
            so[0] = pack_bf(fmaf(e0, dec(u[0].x), e1 * dec(u[1].x)), fmaf(e0, dec(u[0].y), e1 * dec(u[1].y)));
            so[20] = pack_bf(fmaf(e0, dec(u[0].z), e1 * dec(u[1].z)), fmaf(e0, dec(u[0].w), e1 * dec(u[1].w)));
            so[80] = pack_bf(fmaf(e2, dec(u[2].x), e3 * dec(u[3].x)), fmaf(e2, dec(u[2].y), e3 * dec(u[3].y)));
            so[100] = pack_bf(fmaf(e2, dec(u[2].z), e3 * dec(u[3].z)), fmaf(e2, dec(u[2].w), e3 * dec(u[3].w)));
            __syncwarp();
            bar_arrive<6, 320>();
        }
        if (is_own) {
            uint4 v[8];
            poll4<8>(v, S->y + (own * NHEAD + (lane >> 3)) * 32 + 4 * (lane & 7), 128, tag);
            STAMP(26);
            float s[4];
            s[0] = ((dec(v[0].x) + dec(v[1].x)) + (dec(v[2].x) + dec(v[3].x))) + ((dec(v[4].x) + dec(v[5].x)) + (dec(v[6].x) + dec(v[7].x)));
            s[1] = ((dec(v[0].y) + dec(v[1].y)) + (dec(v[2].y) + dec(v[3].y))) + ((dec(v[4].y) + dec(v[5].y)) + (dec(v[6].y) + dec(v[7].y)));
            s[2] = ((dec(v[0].z) + dec(v[1].z)) + (dec(v[2].z) + dec(v[3].z))) + ((dec(v[4].z) + dec(v[5].z)) + (dec(v[6].z) + dec(v[7].z)));
            s[3] = ((dec(v[0].w) + dec(v[1].w)) + (dec(v[2].w) + dec(v[3].w))) + ((dec(v[4].w) + dec(v[5].w)) + (dec(v[6].w) + dec(v[7].w)));
#pragma unroll
            for (int i = 0; i < 4; i++) s[i] += __shfl_xor_sync(0xffffffffu, s[i], 8);
#pragma unroll
            for (int i = 0; i < 4; i++) s[i] += __shfl_xor_sync(0xffffffffu, s[i], 16);
            const float a0 = rbf(bflo(xo0) + rbf(dec(ga4.x) * rbf(s[0]))), a1 = rbf(bflo(xo1) + rbf(dec(ga4.y) * rbf(s[1])));
            const float a2 = rbf(bfhi(xo0) + rbf(dec(ga4.z) * rbf(s[2]))), a3 = rbf(bfhi(xo1) + rbf(dec(ga4.w) * rbf(s[3])));
#pragma unroll
            for (int r = 0; r < X2_REP; r += 4)
                if (r + (lane >> 3) < X2_REP)
                    st_rlx4(S->x2 + (r + (lane >> 3)) * (2 * D_MODEL) + own * 32 + 4 * (lane & 7), enc(a0, tag), enc(a1, tag), enc(a2, tag), enc(a3, tag));
            STAMP(8);
            bar_arrive<4, 288>();
            const int src = lane >> 2;
            const float s0 = __shfl_sync(0xffffffffu, a0, src), s1 = __shfl_sync(0xffffffffu, a1, src);
            const float s2 = __shfl_sync(0xffffffffu, a2, src), s3 = __shfl_sync(0xffffffffu, a3, src);
            const float x2v = c4 == 0 ? s0 : (c4 == 1 ? s1 : (c4 == 2 ? s2 : s3));
            bar_sync<7, 288>();
            const float* p = s_red + lane;
            const float z = ((p[0] + p[32]) + (p[64] + p[96])) + ((p[128] + p[160]) + (p[192] + p[224]));
            out[(lane & 1) * D_MODEL + own * 16 + (lane >> 1)] = __float2bfloat16_rn(x2v + rbf(gb1 * rbf(z)));
            STAMP(12);
        }
        return;
    }

    const int r0 = 2 * tid;
    const uint32_t xp_st = warp * XP_WARP + (c4 * 8 + g) * 4;
    const uint32_t xp_ld = warp * XP_WARP + (g & 3) * XP_COL + c4 * 32;
    uint4 f0, f1;
    if (is_own) {
        *reinterpret_cast<uint32_t*>(smem + SM_XPD + xp_st) = pack_bf(silu_bf(bflo(c0)), silu_bf(bfhi(c0)));
        *reinterpret_cast<uint32_t*>(smem + SM_XPD + XP_COL + xp_st) = pack_bf(silu_bf(bflo(c1)), silu_bf(bfhi(c1)));
        __syncwarp();
        f0 = *reinterpret_cast<const uint4*>(smem + SM_XPD + xp_ld - (g & 2) * XP_COL);
        f1 = *reinterpret_cast<const uint4*>(smem + SM_XPD + xp_ld - (g & 2) * XP_COL + 16);
    }
    ln_partial(bflo(x0), bfhi(x0), bflo(x1), bfhi(x1), s_ml, warp, lane);
    STAMP(20);
    bar_sync<3, NWORK>();
    if (is_own) {
        const int nunit = is_att ? 1 : 19;
#pragma unroll 1
        for (int u = 0; u < nunit; u++) {
            mbar_wait(bar_pm, u & 1);
            if (u == 0) STAMP(22);
            float* red = s_red + (u & 1) * 576;
            gemv32(sbase + (warp < 3 ? SM_PM0 : (warp / 3 - 1) * P_BOX), f0, f1, red, warp, lane);
            bar_sync<3, NWORK>();
            if (tid == 64) mbar_arrive(bar_fm);
            if (u == 0) {
                if (tid < 256) {
                    const uint32_t w = enc(rbf(sum9(red + (tid & 63), 64)), tag);
#pragma unroll
                    for (int r = 0; r < MOD_REP; r += 4)
                        if (r + (tid >> 6) < MOD_REP) st_rlx1(S->sc + (r + (tid >> 6)) * (4 * D_MODEL) + own * 64 + (tid & 63), w);
                }
            } else if (tid < 64) st_rlx1(S->mod + ((2 + cta - NATT) * 18 + u - 1) * 64 + tid, enc(rbf(sum9(red + tid, 64)), tag));
            if (u == 0) STAMP(1);
        }
        if (!is_att) STAMP(13);
    }
    if (is_att) {
        float m0, rs0, m1, rs1;
        ln_stats(s_ml, m0, rs0, m1, rs1);
        const float n00 = rbf((bflo(x0) - m0) * rs0), n01 = rbf((bfhi(x0) - m0) * rs0);
        const float n10 = rbf((bflo(x1) - m1) * rs1), n11 = rbf((bfhi(x1) - m1) * rs1);
        uint4 v[2];
        poll4<2>(v, S->sc + (cta % MOD_REP) * (4 * D_MODEL) + 2 * r0, 2 * D_MODEL, tag);
        STAMP(2);
        *reinterpret_cast<uint32_t*>(smem + SM_XPD + xp_st) =
            pack_bf(rbf(n00 * rbf(1.0f + dec(v[1].x))) + dec(v[0].x), rbf(n01 * rbf(1.0f + dec(v[1].z))) + dec(v[0].z));
        *reinterpret_cast<uint32_t*>(smem + SM_XPD + XP_COL + xp_st) =
            pack_bf(rbf(n10 * rbf(1.0f + dec(v[1].y))) + dec(v[0].y), rbf(n11 * rbf(1.0f + dec(v[1].w))) + dec(v[0].w));
        __syncwarp();
        f0 = *reinterpret_cast<const uint4*>(smem + SM_XPD + xp_ld - (g & 2) * XP_COL);
        f1 = *reinterpret_cast<const uint4*>(smem + SM_XPD + xp_ld - (g & 2) * XP_COL + 16);
        mbar_wait(bar_pq, 0);
        gemv32(sbase + SM_PQ + (warp / 3) * P_BOX, f0, f1, s_red + 576, warp, lane);
        bar_sync<3, NWORK>();
        if (tid == 64) mbar_arrive(bar_fq);
        if (tid < 64)
            st_rlx1(S->q + (tid >> 5) * (NHEAD * DHEAD) + cta * 32 + lane, enc(rbf(sum9(s_red + 576 + lane * 2 + (tid >> 5), 64)), tag));
        if (warp < 8) bar_sync<5, 288>();
        STAMP(3);
    }

    if (is_att && warp < 8) {
        uint32_t qf[8][2], msk[8];
        const int jj = g ^ (2 * c4);
#pragma unroll
        for (int j = 0; j < 8; j++) {
            qf[j][0] = *reinterpret_cast<const uint32_t*>(smem + SM_Q + (8 * (g ^ j) + 2 * c4) * 2);
            qf[j][1] = *reinterpret_cast<const uint32_t*>(smem + SM_Q + (64 + 8 * (g ^ j) + 2 * c4) * 2);
            msk[j] = (j == jj) ? 0x0000ffffu : ((j == (jj ^ 1)) ? 0xffff0000u : 0u);
        }
        const int wq4 = warp & 3;
        const uint32_t koff = sbase + SM_RING + (wq4 * 16 + (lane & 7) + ((lane >> 3) & 1) * 8) * 256 + (lane >> 4) * 128 + (lane & 7) * 16;
        const uint32_t voff = sbase + SM_RING + (wq4 * 16 + (lane & 7) + (lane >> 4) * 8) * 256 + ((lane >> 3) & 1) * 128 + (lane & 7) * 16;
        const bool useful = (c4 == (g >> 1));
        const float SCL = 0.08838834764831845f * 1.4426950408889634f;
        float m_run = -INFINITY, l_run = 0.f, esc = 0.f;
        float oa[4] = {0.f, 0.f, 0.f, 0.f}, ob[4] = {0.f, 0.f, 0.f, 0.f};
        int slot = (warp >> 2) * 2;
        uint32_t ph = 0;
#pragma unroll 1
        for (int it = 0; it < NPAIR / 2; it++) {
            mbar_wait(bar_full + 8 * slot, ph);
            float sa[4] = {0.f, 0.f, 0.f, 0.f}, sb[4] = {0.f, 0.f, 0.f, 0.f};
            const uint32_t ka = koff + ring_pos(slot);
#pragma unroll
            for (int j = 0; j < 8; j++) {
                uint32_t a[4];
                ldsm4(a, ka ^ (j << 4));
                if (j & 1) mma16816(sb, a, qf[j][0], qf[j][1]);
                else mma16816(sa, a, qf[j][0], qf[j][1]);
            }
            __syncwarp();
            if (lane == 0) mbar_arrive(bar_empty + 8 * slot);
            float slo = (g & 1) ? sa[1] + sb[1] : sa[0] + sb[0];
            float shi = (g & 1) ? sa[3] + sb[3] : sa[2] + sb[2];
            slo = useful ? slo * SCL : -INFINITY;
            shi = useful ? shi * SCL : -INFINITY;
            float mx = fmaxf(slo, shi);
            if (__any_sync(0xffffffffu, mx > m_run)) {
#pragma unroll
                for (int o = 16; o; o >>= 1) mx = fmaxf(mx, __shfl_xor_sync(0xffffffffu, mx, o));
                const float alpha = ex2(m_run - mx);
                m_run = mx;
                l_run *= alpha;
#pragma unroll
                for (int i = 0; i < 4; i++) { oa[i] *= alpha; ob[i] *= alpha; }
            }
            const float plo = ex2(slo - m_run), phi = ex2(shi - m_run);
            l_run += plo + phi;
            const uint32_t pk = pack_bf(plo, phi);
            const uint32_t pa = __shfl_sync(0xffffffffu, pk, 9 * c4), pb = __shfl_sync(0xffffffffu, pk, 9 * c4 + 4);
            const uint32_t p0 = __byte_perm(pa, pb, 0x5410), p1 = __byte_perm(pa, pb, 0x7632);
            if (it == NPAIR / 2 - 1) {
#pragma unroll
                for (int o = 16; o; o >>= 1) l_run += __shfl_xor_sync(0xffffffffu, l_run, o);
                if (lane == 0) *reinterpret_cast<float2*>(s_ml + 2 * warp) = make_float2(m_run, l_run);
                bar_sync<2, 256>();
                const float2 w = *reinterpret_cast<const float2*>(s_ml + 2 * (lane & 7));
                float M = w.x;
#pragma unroll
                for (int o = 4; o; o >>= 1) M = fmaxf(M, __shfl_xor_sync(0xffffffffu, M, o));
                esc = ex2(m_run - M);
                if (warp == 0) {
                    float L = w.y * ex2(w.x - M);
#pragma unroll
                    for (int o = 4; o; o >>= 1) L += __shfl_xor_sync(0xffffffffu, L, o);
                    if (lane < 8) st_rlx1(S->part + cta * PART_STRIDE + 128 + lane, enc(lane == 0 ? M : L, tag));
                }
            }
            if (++slot == NSLOT) { slot = 0; ph ^= 1; }
            mbar_wait(bar_full + 8 * slot, ph);
            const uint32_t va = voff + ring_pos(slot);
#pragma unroll
            for (int j = 0; j < 8; j++) {
                uint32_t a[4];
                ldsm4t(a, va ^ (j << 4));
                if (j & 1) mma16816(ob, a, p0 & msk[j], p1 & msk[j]);
                else mma16816(oa, a, p0 & msk[j], p1 & msk[j]);
            }
            __syncwarp();
            if (lane == 0) mbar_arrive(bar_empty + 8 * slot);
            slot += 3;
            if (slot >= NSLOT) { slot -= NSLOT; ph ^= 1; }
        }
        STAMP(4);
        s_red[warp * 128 + 16 * c4 + g] = (oa[0] + ob[0]) * esc;
        s_red[warp * 128 + 16 * c4 + 8 + g] = (oa[1] + ob[1]) * esc;
        s_red[warp * 128 + 64 + 16 * c4 + g] = (oa[2] + ob[2]) * esc;
        s_red[warp * 128 + 64 + 16 * c4 + 8 + g] = (oa[3] + ob[3]) * esc;
        bar_sync<2, 256>();
        if (tid < 128) {
            const float* p = s_red + tid;
            st_rlx1(S->part + cta * PART_STRIDE + tid,
                    enc(((p[0] + p[128]) + (p[256] + p[384])) + ((p[512] + p[640]) + (p[768] + p[896])), tag));
        }
        STAMP(5);
    }

    if (is_att) {
        const int G = 2 * warp + ((lane >> 3) & 1);
        const uint32_t wa = sbase + SM_WO + (G >= 9 ? WO_BOX + (G - 9) * 16 : G * 16) + ((lane & 7) + (lane >> 4) * 8) * 144;
        uint32_t wf[8][4];
        mbar_wait(bar_w, 0);
        mbar_wait(bar_w + 8, 0);
#pragma unroll
        for (int s = 0; s < 8; s++) ldsm4t(wf[s], wa + s * 16 * 144);
        STAMP(19);
        bar_sync<6, 320>();
        STAMP(6);
        float d[4][4];
        const uint4* p = reinterpret_cast<const uint4*>(smem + SM_O + (g & 1) * 320 + c4 * 80);
#pragma unroll
        for (int i = 0; i < 4; i++) {
            const uint4 v = p[i];
            d[i][0] = d[i][1] = d[i][2] = d[i][3] = 0.f;
            mma16816(d[i], wf[2 * i], v.x, v.y);
            mma16816(d[i], wf[2 * i + 1], v.z, v.w);
        }
        if (c4 == 0) {
            uint32_t* q = S->y + ((9 * qq + warp) * NHEAD + head) * 32 + 2 * g;
            st_rlx2(q, enc((d[0][0] + d[1][0]) + (d[2][0] + d[3][0]), tag), enc((d[0][1] + d[1][1]) + (d[2][1] + d[3][1]), tag));
            st_rlx2(q + 16, enc((d[0][2] + d[1][2]) + (d[2][2] + d[3][2]), tag), enc((d[0][3] + d[1][3]) + (d[2][3] + d[3][3]), tag));
        }
        STAMP(7);
    }
    if (is_own) {
        if (warp < 8) {
            bar_sync<4, 288>();
            uint4 v[3];
            poll4<3>(v, S->z + (own * NMLP + warp * 12 + (lane >> 3)) * 32 + 4 * (lane & 7), 128, tag);
            STAMP(28);
            float s[4];
            s[0] = dec(v[0].x) + dec(v[1].x) + dec(v[2].x);
            s[1] = dec(v[0].y) + dec(v[1].y) + dec(v[2].y);
            s[2] = dec(v[0].z) + dec(v[1].z) + dec(v[2].z);
            s[3] = dec(v[0].w) + dec(v[1].w) + dec(v[2].w);
#pragma unroll
            for (int i = 0; i < 4; i++) s[i] += __shfl_xor_sync(0xffffffffu, s[i], 8);
#pragma unroll
            for (int i = 0; i < 4; i++) s[i] += __shfl_xor_sync(0xffffffffu, s[i], 16);
            if (lane < 8) *reinterpret_cast<float4*>(s_red + warp * 32 + 4 * lane) = make_float4(s[0], s[1], s[2], s[3]);
            __syncwarp();
            bar_arrive<7, 288>();
        }
    } else {
        uint32_t w1f[12][4], w2f[12][4];
        const uint32_t w1a = sbase + SM_W1 + (warp * 64 + (lane & 7) + (lane >> 4) * 8) * 96 + ((lane >> 3) & 1) * 16;
        mbar_wait(bar_w + 8 * (2 + warp / 3), 0);
#pragma unroll
        for (int s = 0; s < 4; s++)
#pragma unroll
            for (int t = 0; t < 3; t++) ldsm4t(w1f[3 * s + t], w1a + s * 16 * 96 + t * 32);
        STAMP(16);
        uint32_t w2a[4];
#pragma unroll
        for (int t = 0; t < 4; t++) {
            const int G = 2 * (warp * 4 + t) + ((lane >> 3) & 1);
            w2a[t] = sbase + SM_W2 + (G / 9) * W2_BOX + (G % 9) * 16 + ((lane & 7) + (lane >> 4) * 8) * 144;
        }
        const bool w2_early = __all_sync(0xffffffffu, mbar_test(bar_w + 8 * 5, 0) & mbar_test(bar_w + 8 * 6, 0) & mbar_test(bar_w + 8 * 7, 0));
        if (w2_early) {
#pragma unroll
            for (int i = 0; i < 12; i++) ldsm4t(w2f[i], w2a[i / 3] + (i % 3) * 16 * 144);
        }
        const uint32_t ca = *reinterpret_cast<const uint32_t*>(smem + SM_XPC + xp_st);
        const uint32_t cb = *reinterpret_cast<const uint32_t*>(smem + SM_XPC + XP_COL + xp_st);
        uint4 v[1];
        poll4<1>(v, S->x2 + (cta % X2_REP) * (2 * D_MODEL) + 4 * tid, 0, tag);
        STAMP(27);
        const float a0 = dec(v[0].x), b0 = dec(v[0].y), a1 = dec(v[0].z), b1 = dec(v[0].w);
        {
            const float pa0 = a0 * bflo(ca), pa1 = a1 * bfhi(ca), pb0 = b0 * bflo(cb), pb1 = b1 * bfhi(cb);
            const uint32_t ha = pack_bf(pa0, pa1), hb = pack_bf(pb0, pb1);
            unsigned char* p = smem + SM_XPD + xp_st;
            *reinterpret_cast<uint32_t*>(p) = ha;
            *reinterpret_cast<uint32_t*>(p + XP_COL) = hb;
            *reinterpret_cast<uint32_t*>(p + 2 * XP_COL) = pack_bf(pa0 - bflo(ha), pa1 - bfhi(ha));
            *reinterpret_cast<uint32_t*>(p + 3 * XP_COL) = pack_bf(pb0 - bflo(hb), pb1 - bfhi(hb));
        }
        __syncwarp();
        const unsigned char* fp = smem + (g < 4 ? SM_XPD : SM_XPC) + xp_ld;
        f0 = *reinterpret_cast<const uint4*>(fp);
        f1 = *reinterpret_cast<const uint4*>(fp + 16);
        float d1[3][4];
#pragma unroll
        for (int t = 0; t < 3; t++) {
            d1[t][0] = d1[t][1] = d1[t][2] = d1[t][3] = 0.f;
            mma16816(d1[t], w1f[t], f0.x, f0.y);
        }
#pragma unroll
        for (int t = 0; t < 3; t++) mma16816(d1[t], w1f[3 + t], f0.z, f0.w);
#pragma unroll
        for (int t = 0; t < 3; t++) mma16816(d1[t], w1f[6 + t], f1.x, f1.y);
#pragma unroll
        for (int t = 0; t < 3; t++) mma16816(d1[t], w1f[9 + t], f1.z, f1.w);
        ln_partial(a0, a1, b0, b1, s_ml, warp, lane);
        float* s_hp = reinterpret_cast<float*>(smem + SM_HP);
#pragma unroll
        for (int t = 0; t < 3; t++) {
            *reinterpret_cast<float2*>(s_hp + warp * 384 + t * 128 + 2 * lane) = make_float2(d1[t][0], d1[t][1]);
            *reinterpret_cast<float2*>(s_hp + warp * 384 + t * 128 + 64 + 2 * lane) = make_float2(d1[t][2], d1[t][3]);
        }
        STAMP(17);
        bar_sync<3, NWORK>();
        if (warp < 6) {
            float2 t[9];
#pragma unroll
            for (int w = 0; w < 9; w++) t[w] = *reinterpret_cast<const float2*>(s_hp + w * 384 + 2 * tid);
            float m0, rs0, m1, rs1;
            ln_stats(s_ml, m0, rs0, m1, rs1);
            float u0 = ((t[0].x + t[1].x) + (t[2].x + t[3].x)) + ((t[4].x + t[5].x) + (t[6].x + t[7].x)) + t[8].x;
            float u1 = ((t[0].y + t[1].y) + (t[2].y + t[3].y)) + ((t[4].y + t[5].y) + (t[6].y + t[7].y)) + t[8].y;
            u0 *= c4 == 3 ? 1.0f : (c4 == 2 ? -rs0 * m0 : rs0);
            u1 *= c4 == 3 ? 1.0f : (c4 == 2 ? -rs1 * m1 : rs1);
            float u = (c4 & 1 ? u1 : u0) + __shfl_xor_sync(0xffffffffu, c4 & 1 ? u0 : u1, 1);
            u += __shfl_xor_sync(0xffffffffu, u, 2);
            const int k = tid >> 2, r = k & 15;
            if (c4 < 2)
                reinterpret_cast<bf16*>(smem + SM_H1)[c4 * 48 + ((r & 7) >> 1) * 12 + (k >> 4) * 4 + (r >> 3) * 2 + (r & 1)] =
                    __float2bfloat16_rn(fmaxf(u, 0.0f));
        }
        if (!w2_early) {
            mbar_wait(bar_w + 8 * 5, 0);
            mbar_wait(bar_w + 8 * 6, 0);
            mbar_wait(bar_w + 8 * 7, 0);
#pragma unroll
            for (int i = 0; i < 12; i++) ldsm4t(w2f[i], w2a[i / 3] + (i % 3) * 16 * 144);
        }
        STAMP(18);
        bar_sync<3, NWORK>();
        STAMP(10);
        const uint2* p = reinterpret_cast<const uint2*>(smem + SM_H1 + (g & 1) * 96 + c4 * 24);
        const uint2 h0 = p[0], h1 = p[1], h2 = p[2];
        float d[4][4];
#pragma unroll
        for (int t = 0; t < 4; t++) {
            d[t][0] = d[t][1] = d[t][2] = d[t][3] = 0.f;
            mma16816(d[t], w2f[3 * t], h0.x, h0.y);
        }
#pragma unroll
        for (int t = 0; t < 4; t++) mma16816(d[t], w2f[3 * t + 1], h1.x, h1.y);
#pragma unroll
        for (int t = 0; t < 4; t++) mma16816(d[t], w2f[3 * t + 2], h2.x, h2.y);
        if (c4 == 0) {
#pragma unroll
            for (int t = 0; t < 4; t++) {
                uint32_t* q = S->z + ((warp * 4 + t) * NMLP + cta) * 32 + 2 * g;
                st_rlx2(q, enc(d[t][0], tag), enc(d[t][1], tag));
                st_rlx2(q + 16, enc(d[t][2], tag), enc(d[t][3], tag));
            }
        }
        if (cta == 0 && tid == 0) {
            st_rlx1(S->epoch, epoch);
            st_rlx1(S->prog + ((epoch + 1) & 1) * 32, 0);
            st_rlx1(S->prog + (2 + ((epoch + 1) & 1)) * 32, 0);
        }
        STAMP(11); CSTAMP(31);
    }
}

typedef CUresult (*EncodeFn)(CUtensorMap*, CUtensorMapDataType, cuuint32_t, void*, const cuuint64_t*, const cuuint64_t*,
                             const cuuint32_t*, const cuuint32_t*, CUtensorMapInterleave, CUtensorMapSwizzle,
                             CUtensorMapL2promotion, CUtensorMapFloatOOBfill);

void make_map(EncodeFn fn, CUtensorMap* m, const void* p, uint64_t cols, uint64_t rows, uint32_t bcols, uint32_t brows,
              CUtensorMapSwizzle swz) {
    const cuuint64_t dims[2] = {cols, rows};
    const cuuint64_t strides[1] = {cols * 2};
    const cuuint32_t box[2] = {bcols, brows};
    const cuuint32_t es[2] = {1, 1};
    fn(m, CU_TENSOR_MAP_DATA_TYPE_BFLOAT16, 2, const_cast<void*>(p), dims, strides, box, es, CU_TENSOR_MAP_INTERLEAVE_NONE,
       swz, CU_TENSOR_MAP_L2_PROMOTION_NONE, CU_TENSOR_MAP_FLOAT_OOB_FILL_NONE);
}

}

extern "C" void kernel_launch(void* const* d_in, const int* in_sizes, int n_in, void* d_out, int out_size) {
    (void)in_sizes; (void)n_in; (void)out_size;
    static EncodeFn encode = nullptr;
    static Scratch* scratch = nullptr;
    if (!encode) {
        cudaGetSymbolAddress(reinterpret_cast<void**>(&scratch), g_scratch);
        void* fn = nullptr;
        cudaDriverEntryPointQueryResult st;
        cudaGetDriverEntryPoint("cuTensorMapEncodeTiled", &fn, cudaEnableDefault, &st);
        encode = reinterpret_cast<EncodeFn>(fn);
        cudaFuncSetAttribute(adaln_block_kernel, cudaFuncAttributeMaxDynamicSharedMemorySize, SM_TOTAL);
    }
    CUtensorMap mwm, mwq, mwo, mw1, mw2;
    make_map(encode, &mwm, d_in[9], NMODC, D_MODEL, 32, 192, CU_TENSOR_MAP_SWIZZLE_64B);
    make_map(encode, &mwq, d_in[3], NHEAD * DHEAD, D_MODEL, 32, 192, CU_TENSOR_MAP_SWIZZLE_64B);
    make_map(encode, &mwo, d_in[4], D_MODEL, NHEAD * DHEAD, 72, 128, CU_TENSOR_MAP_SWIZZLE_NONE);
    make_map(encode, &mw1, d_in[6], DFF, D_MODEL, 48, 192, CU_TENSOR_MAP_SWIZZLE_NONE);
    make_map(encode, &mw2, d_in[7], D_MODEL, DFF, 72, 48, CU_TENSOR_MAP_SWIZZLE_NONE);
    adaln_block_kernel<<<NCTA, NTHR, SM_TOTAL>>>(mwm, mwq, mwo, mw1, mw2, (const bf16*)d_in[0], (const bf16*)d_in[1],
                                                 (const bf16*)d_in[2], (const bf16*)d_in[8], (bf16*)d_out, scratch);
}
```

```cpp
#include <cuda_runtime.h>
#include <cuda_bf16.h>
#include <cuda.h>
#include <stdint.h>

namespace {

typedef __nv_bfloat16 bf16;

constexpr int D_MODEL = 576;
constexpr int NHEAD   = 32;
constexpr int DHEAD   = 128;
constexpr int SKV     = 16384;
constexpr int DFF     = 4608;
constexpr int NMODC   = 6 * D_MODEL;

constexpr int NCTA  = 132;
constexpr int NATT  = 128;
constexpr int NMLP  = 96;
constexpr int OWN0  = 96;
constexpr int NOWN  = 36;
constexpr int NTHR  = 352;
constexpr int NWORK = 288;

constexpr int TILE_KEYS  = 64;
constexpr int TILE_BYTES = TILE_KEYS * DHEAD * 2;
constexpr int NSLOT      = 13;
constexpr int NPAIR      = (SKV / 2) / TILE_KEYS;
constexpr int NTILE      = 2 * NPAIR;
constexpr int SLOT_ROT   = 4;

constexpr int WIN  = 4;
constexpr int WIN0 = 2;
constexpr int WINW = 2;
constexpr uint32_t RANK_T = 0x22222233u;
constexpr int FB_P = 2, FB_FIRST = 16;
constexpr int FB_TOTAL = ((NTILE - FB_FIRST) / FB_P + 1) * NATT;
constexpr int FB_END = 232, FB_MIN = 2, FB_MAX = 8;
constexpr float FB_WIN = 3.8f, FB_KP = 0.6f, FB_KP_END = 3.0f, FB_KI = 0.05f;

constexpr int SM_RING  = 0;
constexpr int SM_WO    = 0;
constexpr int WO_BOX   = 128 * 144;
constexpr int SM_W1    = SM_WO + 2 * WO_BOX;
constexpr int W1_BOX   = 192 * 96;
constexpr int SM_W2    = SM_W1 + 3 * W1_BOX;
constexpr int W2_BOX   = 9 * 16 * 128;
constexpr int SM_WEND  = SM_W2 + 3 * W2_BOX;
constexpr int SM_HP    = SM_WEND;
constexpr int P_BOX    = 192 * 64;
constexpr int SM_PM0   = 12 * TILE_BYTES;
constexpr int SM_PQ    = 4 * TILE_BYTES - 3 * P_BOX;
constexpr int XP_COL   = 144;
constexpr int XP_WARP  = 4 * XP_COL;
constexpr int SM_XPD   = NSLOT * TILE_BYTES;
constexpr int SM_XPC   = SM_XPD + 9 * XP_WARP;
constexpr int SM_RED   = SM_XPC + 9 * XP_WARP;
constexpr int SM_ML    = SM_RED + 4608;
constexpr int SM_Q     = SM_ML + 256;
constexpr int SM_O     = SM_Q + 256;
constexpr int SM_H1    = SM_O + 640;
constexpr int SM_BAR   = SM_H1 + 192;
constexpr int NBAR     = 2 * NSLOT + 8 + 7;
constexpr int SM_TOTAL = SM_BAR + 8 * NBAR;
static_assert(SM_WEND == 9 * TILE_BYTES && SM_W2 % 1024 == 0 && W1_BOX == WO_BOX && W2_BOX == WO_BOX, "layout");
static_assert(SM_PQ >= 2 * P_BOX && SM_PQ % 512 == 0, "layout");
static_assert(SM_TOTAL <= 232448, "smem");
static_assert((NTILE - NSLOT + SLOT_ROT) % NSLOT == 0, "tile NTILE-13 must sit at ring position 0");

constexpr int PART_STRIDE = 160;

struct Scratch {
    uint32_t epoch[32];
    uint32_t prog[2 * 32];
    uint32_t mod[NMODC * 2];
    uint32_t q[2 * NHEAD * DHEAD];
    uint32_t part[NATT * PART_STRIDE];
    uint32_t y[NOWN * NHEAD * 32];
    uint32_t x2[D_MODEL * 2];
    uint32_t z[NOWN * NMLP * 32];
};
__device__ __align__(128) Scratch g_scratch;

constexpr int SPIN_LIMIT = 1 << 22;

__device__ __forceinline__ uint32_t smem_u32(const void* p) { return (uint32_t)__cvta_generic_to_shared(p); }

__device__ __forceinline__ void mbar_init(uint32_t a, uint32_t cnt) {
    asm volatile("mbarrier.init.shared::cta.b64 [%0], %1;" ::"r"(a), "r"(cnt) : "memory");
}
__device__ __forceinline__ void mbar_expect(uint32_t a, uint32_t bytes) {
    asm volatile("mbarrier.arrive.expect_tx.shared::cta.b64 _, [%0], %1;" ::"r"(a), "r"(bytes) : "memory");
}
__device__ __forceinline__ void mbar_arrive(uint32_t a) {
    asm volatile("mbarrier.arrive.shared::cta.b64 _, [%0];" ::"r"(a) : "memory");
}
__device__ __forceinline__ uint32_t mbar_test(uint32_t a, uint32_t parity) {
    uint32_t ok;
    asm volatile("{.reg .pred p; mbarrier.test_wait.parity.shared::cta.b64 p, [%1], %2; selp.u32 %0, 1, 0, p;}"
                 : "=r"(ok) : "r"(a), "r"(parity) : "memory");
    return ok;
}
__device__ __forceinline__ void mbar_wait(uint32_t a, uint32_t parity) {
    int it = 0;
    while (true) {
        uint32_t ok;
        asm volatile("{.reg .pred p; mbarrier.try_wait.parity.shared::cta.b64 p, [%1], %2; selp.u32 %0, 1, 0, p;}"
                     : "=r"(ok) : "r"(a), "r"(parity) : "memory");
        if (ok) break;
        if (++it > SPIN_LIMIT) __trap();
    }
}
__device__ __forceinline__ void bulk_load(uint32_t dst, const void* src, uint32_t bytes, uint32_t bar, uint64_t pol) {
    asm volatile("cp.async.bulk.shared::cluster.global.mbarrier::complete_tx::bytes.L2::cache_hint [%0], [%1], %2, [%3], %4;"
                 ::"r"(dst), "l"(src), "r"(bytes), "r"(bar), "l"(pol) : "memory");
}
__device__ __forceinline__ void tensor_load(uint32_t dst, const CUtensorMap* map, int c0, int c1, uint32_t bar) {
    asm volatile("cp.async.bulk.tensor.2d.shared::cluster.global.mbarrier::complete_tx::bytes [%0], [%1, {%3, %4}], [%2];"
                 ::"r"(dst), "l"(map), "r"(bar), "r"(c0), "r"(c1) : "memory");
}
__device__ __forceinline__ void tensor_load3(uint32_t dst, const CUtensorMap* map, int c1, uint32_t bar) {
    asm volatile("cp.async.bulk.tensor.3d.shared::cluster.global.mbarrier::complete_tx::bytes [%0], [%1, {%4, %3, %4}], [%2];"
                 ::"r"(dst), "l"(map), "r"(bar), "r"(c1), "r"(0) : "memory");
}
template <int ID, int N>
__device__ __forceinline__ void bar_sync() { asm volatile("bar.sync %0, %1;" ::"n"(ID), "n"(N) : "memory"); }
template <int ID, int N>
__device__ __forceinline__ void bar_arrive() { asm volatile("bar.arrive %0, %1;" ::"n"(ID), "n"(N) : "memory"); }

__device__ __forceinline__ void ldsm4(uint32_t (&r)[4], uint32_t addr) {
    asm volatile("ldmatrix.sync.aligned.m8n8.x4.shared.b16 {%0,%1,%2,%3}, [%4];"
                 : "=r"(r[0]), "=r"(r[1]), "=r"(r[2]), "=r"(r[3]) : "r"(addr) : "memory");
}
__device__ __forceinline__ void ldsm4t(uint32_t (&r)[4], uint32_t addr) {
    asm volatile("ldmatrix.sync.aligned.m8n8.x4.trans.shared.b16 {%0,%1,%2,%3}, [%4];"
                 : "=r"(r[0]), "=r"(r[1]), "=r"(r[2]), "=r"(r[3]) : "r"(addr) : "memory");
}
__device__ __forceinline__ void mma16816(float (&d)[4], const uint32_t (&a)[4], uint32_t b0, uint32_t b1) {
    asm volatile("mma.sync.aligned.m16n8k16.row.col.f32.bf16.bf16.f32 {%0,%1,%2,%3}, {%4,%5,%6,%7}, {%8,%9}, {%0,%1,%2,%3};"
                 : "+f"(d[0]), "+f"(d[1]), "+f"(d[2]), "+f"(d[3])
                 : "r"(a[0]), "r"(a[1]), "r"(a[2]), "r"(a[3]), "r"(b0), "r"(b1));
}

__device__ __forceinline__ uint4 ld_rlx4(const uint32_t* p) {
    uint4 v;
    asm volatile("ld.relaxed.gpu.global.v4.u32 {%0,%1,%2,%3}, [%4];" : "=r"(v.x), "=r"(v.y), "=r"(v.z), "=r"(v.w) : "l"(p) : "memory");
    return v;
}
__device__ __forceinline__ uint2 ld_rlx2(const uint32_t* p) {
    uint2 v;
    asm volatile("ld.relaxed.gpu.global.v2.u32 {%0,%1}, [%2];" : "=r"(v.x), "=r"(v.y) : "l"(p) : "memory");
    return v;
}
__device__ __forceinline__ uint32_t ld_rlx1(const uint32_t* p) {
    uint32_t v;
    asm volatile("ld.relaxed.gpu.global.u32 %0, [%1];" : "=r"(v) : "l"(p) : "memory");
    return v;
}
__device__ __forceinline__ void st_rlx4(uint32_t* p, uint32_t a, uint32_t b, uint32_t c, uint32_t d) {
    asm volatile("st.relaxed.gpu.global.v4.u32 [%0], {%1,%2,%3,%4};" ::"l"(p), "r"(a), "r"(b), "r"(c), "r"(d) : "memory");
}
__device__ __forceinline__ void st_rlx1(uint32_t* p, uint32_t a) {
    asm volatile("st.relaxed.gpu.global.u32 [%0], %1;" ::"l"(p), "r"(a) : "memory");
}
__device__ __forceinline__ uint32_t enc(float v, uint32_t tag) { return (__float_as_uint(v) & ~3u) | tag; }
__device__ __forceinline__ float dec(uint32_t w) { return __uint_as_float(w & ~3u); }
__device__ __forceinline__ uint32_t bad4(const uint4& v, uint32_t tag) { return (v.x ^ tag) | (v.y ^ tag) | (v.z ^ tag) | (v.w ^ tag); }
template <int N>
__device__ __forceinline__ void poll4(uint4 (&v)[N], const uint32_t* p, int stride, uint32_t tag) {
    uint32_t bad[N];
#pragma unroll
    for (int i = 0; i < N; i++) { v[i] = make_uint4(0, 0, 0, 0); bad[i] = 1; }
    int it = 0;
    while (true) {
        uint32_t any = 0;
#pragma unroll
        for (int i = 0; i < N; i++)
            asm volatile("{.reg .pred q; setp.ne.u32 q, %5, 0; @q ld.relaxed.gpu.global.v4.u32 {%0,%1,%2,%3}, [%4];}"
                         : "+r"(v[i].x), "+r"(v[i].y), "+r"(v[i].z), "+r"(v[i].w) : "l"(p + i * stride), "r"(bad[i]) : "memory");
#pragma unroll
        for (int i = 0; i < N; i++) { bad[i] = bad4(v[i], tag) & 3u; any |= bad[i]; }
        if (__all_sync(0xffffffffu, any == 0)) break;
        if (++it > SPIN_LIMIT) __trap();
    }
}

__device__ __forceinline__ float rbf(float v) {
    uint32_t r;
    asm("cvt.rn.bf16x2.f32 %0, %1, %2;" : "=r"(r) : "f"(v), "f"(0.0f));
    return __uint_as_float(r);
}
__device__ __forceinline__ float bflo(uint32_t w) { return __uint_as_float(w << 16); }
__device__ __forceinline__ float bfhi(uint32_t w) { return __uint_as_float(w & 0xffff0000u); }
__device__ __forceinline__ uint32_t pack_bf(float lo, float hi) {
    uint32_t r;
    asm("cvt.rn.bf16x2.f32 %0, %1, %2;" : "=r"(r) : "f"(hi), "f"(lo));
    return r;
}
__device__ __forceinline__ float ex2(float x) {
    float r;
    asm("ex2.approx.ftz.f32 %0, %1;" : "=f"(r) : "f"(x));
    return r;
}
__device__ __forceinline__ float rcp(float x) {
    float r;
    asm("rcp.approx.ftz.f32 %0, %1;" : "=f"(r) : "f"(x));
    return r;
}
__device__ __forceinline__ float sqr(float x) {
    float r;
    asm("sqrt.approx.ftz.f32 %0, %1;" : "=f"(r) : "f"(x));
    return r;
}
__device__ __forceinline__ uint32_t ldg32(const void* p) {
    uint32_t v;
    asm volatile("ld.global.nc.u32 %0, [%1];" : "=r"(v) : "l"(p));
    return v;
}
__device__ __forceinline__ float silu_bf(float v) { return __fdividef(v, 1.0f + __expf(-v)); }

__device__ __forceinline__ void ln_partial(float a0, float a1, float b0, float b1, float* ml, int warp, int lane) {
    const bool odd = lane & 1;
    const float s0 = a0 + a1, q0 = fmaf(a0, a0, a1 * a1), s1 = b0 + b1, q1 = fmaf(b0, b0, b1 * b1);
    float s = (odd ? s1 : s0) + __shfl_xor_sync(0xffffffffu, odd ? s0 : s1, 1);
    float q = (odd ? q1 : q0) + __shfl_xor_sync(0xffffffffu, odd ? q0 : q1, 1);
#pragma unroll
    for (int o = 2; o < 32; o <<= 1) {
        s += __shfl_xor_sync(0xffffffffu, s, o);
        q += __shfl_xor_sync(0xffffffffu, q, o);
    }
    if (lane < 2) *reinterpret_cast<float2*>(ml + 4 * warp + 2 * lane) = make_float2(s, q);
}
__device__ __forceinline__ void ln_stats(const float* ml, float& m0, float& r0, float& m1, float& r1) {
    float4 t[9];
#pragma unroll
    for (int i = 0; i < 9; i++) t[i] = *reinterpret_cast<const float4*>(ml + 4 * i);
#pragma unroll
    for (int o = 1; o < 9; o <<= 1)
#pragma unroll
        for (int i = 0; i + o < 9; i += 2 * o) { t[i].x += t[i + o].x; t[i].y += t[i + o].y; t[i].z += t[i + o].z; t[i].w += t[i + o].w; }
    m0 = t[0].x * (1.0f / D_MODEL);
    m1 = t[0].z * (1.0f / D_MODEL);
    r0 = rcp(rbf(sqr(rbf(rbf(fmaxf(fmaf(-m0, m0, t[0].y * (1.0f / D_MODEL)), 0.0f)) + 1e-5f))));
    r1 = rcp(rbf(sqr(rbf(rbf(fmaxf(fmaf(-m1, m1, t[0].w * (1.0f / D_MODEL)), 0.0f)) + 1e-5f))));
    m0 = rbf(m0);
    m1 = rbf(m1);
}

__device__ __forceinline__ void gemv32(uint32_t box, const uint4& f0, const uint4& f1, float* red, int warp, int lane) {
    const uint32_t a0 = box + ((warp % 3) * 64 + (lane & 7) + (lane >> 4) * 8) * 64 + ((((lane >> 3) & 1) ^ ((lane & 7) >> 1)) << 4);
    const uint32_t bf[8] = {f0.x, f0.y, f0.z, f0.w, f1.x, f1.y, f1.z, f1.w};
    float d[2][4] = {{0.f, 0.f, 0.f, 0.f}, {0.f, 0.f, 0.f, 0.f}};
#pragma unroll
    for (int s = 0; s < 4; s++)
#pragma unroll
        for (int t = 0; t < 2; t++) {
            uint32_t a[4];
            ldsm4t(a, (a0 + s * 1024) ^ (t << 5));
            mma16816(d[t], a, bf[2 * s], bf[2 * s + 1]);
        }
    if ((lane & 3) == 0) {
#pragma unroll
        for (int t = 0; t < 2; t++) {
            *reinterpret_cast<float2*>(red + warp * 64 + (16 * t + (lane >> 2)) * 2) = make_float2(d[t][0], d[t][1]);
            *reinterpret_cast<float2*>(red + warp * 64 + (16 * t + 8 + (lane >> 2)) * 2) = make_float2(d[t][2], d[t][3]);
        }
    }
}
__device__ __forceinline__ float sum9(const float* p, int stride) {
    float v[9];
#pragma unroll
    for (int i = 0; i < 9; i++) v[i] = p[i * stride];
    return ((v[0] + v[1]) + (v[2] + v[3])) + ((v[4] + v[5]) + (v[6] + v[7])) + v[8];
}

__device__ __forceinline__ uint32_t ring_pos(int slot) { return (slot + SLOT_ROT >= NSLOT ? slot + SLOT_ROT - NSLOT : slot + SLOT_ROT) * TILE_BYTES; }

__global__ void __launch_bounds__(NTHR, 1)
adaln_block_kernel(const __grid_constant__ CUtensorMap map_wm, const __grid_constant__ CUtensorMap map_wq,
                   const __grid_constant__ CUtensorMap map_wo, const __grid_constant__ CUtensorMap map_w1,
                   const __grid_constant__ CUtensorMap map_w2, const bf16* __restrict__ x, const bf16* __restrict__ kc,
                   const bf16* __restrict__ vc, const bf16* __restrict__ cnd, bf16* __restrict__ out, Scratch* S) {
    extern __shared__ __align__(1024) unsigned char smem[];
    uint32_t sbase = smem_u32(smem);
    asm volatile("" : "+r"(sbase));
    const int tid = threadIdx.x, warp = tid >> 5, lane = tid & 31;
    const int g = lane >> 2, c4 = lane & 3;
    const int cta = blockIdx.x;
    const bool is_att = cta < NATT, is_mlp = cta < NMLP, is_own = cta >= OWN0;
    const int head = cta >> 2, qq = cta & 3, bat = (cta >> 1) & 1, half = cta & 1;
    const int own = cta - OWN0;

    const uint32_t bar_full = sbase + SM_BAR, bar_empty = bar_full + 8 * NSLOT, bar_w = bar_empty + 8 * NSLOT;
    const uint32_t bar_h1 = bar_w + 64, bar_near = bar_h1 + 8, bar_x2 = bar_near + 8;
    const uint32_t bar_fm = bar_x2 + 8, bar_fq = bar_fm + 8;
    const uint32_t bar_pm = bar_fq + 8, bar_pq = bar_pm + 8;
    float* s_red = reinterpret_cast<float*>(smem + SM_RED);
    float* s_ml = reinterpret_cast<float*>(smem + SM_ML);

    if (warp == 10) {
        if (lane == 0) {
            mbar_init(bar_pm, 1);
            mbar_init(bar_pq, 1);
            asm volatile("fence.mbarrier_init.release.cluster;" ::: "memory");
            if (is_own) {
                mbar_expect(bar_pm, 3 * P_BOX);
#pragma unroll
                for (int i = 0; i < 3; i++) tensor_load(sbase + (i == 0 ? SM_PM0 : (i - 1) * P_BOX), &map_wm, own * 32, i * 192, bar_pm);
            }
            if (is_att) {
                mbar_expect(bar_pq, 3 * P_BOX);
#pragma unroll
                for (int i = 0; i < 3; i++) tensor_load(sbase + SM_PQ + i * P_BOX, &map_wq, cta * 32, i * 192, bar_pq);
            }
        }
        __syncwarp();
        bar_sync<1, NTHR>();
        if (lane != 0) return;
        if (!is_att) {
#pragma unroll 1
            for (int u = 0; u < 18; u++) {
                mbar_wait(bar_fm, u & 1);
                mbar_expect(bar_pm, 3 * P_BOX);
#pragma unroll
                for (int i = 0; i < 3; i++)
                    tensor_load(sbase + (i == 0 ? SM_PM0 : (i - 1) * P_BOX), &map_wm, ((2 + cta - NATT) * 18 + u) * 32, i * 192, bar_pm);
            }
            return;
        }
        uint64_t pol;
        asm volatile("createpolicy.fractional.L2::evict_first.b64 %0, 1.0;" : "=l"(pol));
        const size_t base = ((size_t)(bat * NHEAD + head) * SKV + (size_t)half * TILE_KEYS) * DHEAD * 2;
        const int shift = (head & 1) * 96 + (head & 2);
        const char* ksrc = reinterpret_cast<const char*>(kc) + base;
        const char* vsrc = reinterpret_cast<const char*>(vc) + base;
        const int nitem = NTILE + (is_mlp ? 8 : 2);
        int slot = 0, landed = 0, wslot = 0, win = WIN, total = 0, mine = 0;
        uint32_t ph = 1, wph = 0;
        uint32_t* prog = S->prog;
        float integ = 0.f;
#pragma unroll 1
        for (int k = 0; k < nitem; k++) {
            if (k == NTILE) win = WINW;
            if (k >= NTILE + 4 && win < 8) {
                int it = 0;
                while (landed + win <= k) {
                    if (mbar_test(bar_x2, 0)) { win = 8; break; }
                    if (mbar_test(bar_w + 8 * (landed - NTILE), 0)) landed++;
                    if (++it > SPIN_LIMIT) __trap();
                }
            }
            while (landed + win <= k) {
                if (landed < NTILE) {
                    mbar_wait(bar_full + 8 * wslot, wph);
                    if (++wslot == NSLOT) { wslot = 0; wph ^= 1; }
                } else mbar_wait(bar_w + 8 * (landed - NTILE), 0);
                landed++;
            }
            if (k >= NSLOT) mbar_wait(bar_empty + 8 * slot, ph);
            else if (k == WIN0) mbar_wait(bar_pq, 0);
            else if (k == 8) { if (is_own) mbar_wait(bar_fm, 0); }
            else if (k == 10) {
                asm volatile("prefetch.tensormap [%0];" ::"l"(&map_wo) : "memory");
                asm volatile("prefetch.tensormap [%0];" ::"l"(&map_w1) : "memory");
                asm volatile("prefetch.tensormap [%0];" ::"l"(&map_w2) : "memory");
                prog += ((ld_rlx1(S->epoch) + 1) & 1) * 32;
                mbar_wait(bar_fq, 0);
            }
            if (k < NTILE) {
                mbar_expect(bar_full + 8 * slot, TILE_BYTES);
                bulk_load(sbase + SM_RING + ring_pos(slot), ((k & 1) ? vsrc : ksrc) + (size_t)((k >> 1) ^ shift) * (2 * TILE_BYTES), TILE_BYTES,
                          bar_full + 8 * slot, pol);
                if (++slot == NSLOT) { slot = 0; ph ^= 1; }
                if ((k & (FB_P - 1)) == FB_P - 1 && k >= FB_FIRST - 1) {
                    if (mine) {
                        const float lag = (float)(total - mine * NATT + NATT / 2 + 1) * (1.0f / NATT);
                        integ = fminf(fmaxf(fmaf(FB_KI, lag, integ), -2.0f), 3.0f);
                        win = min(max(__float2int_rn(FB_WIN + (k >= FB_END ? FB_KP_END : FB_KP) * lag + integ), FB_MIN), FB_MAX);
                    }
                    mine++;
                    asm volatile("atom.relaxed.gpu.global.add.u32 %0, [%1], 1;" : "=r"(total) : "l"(prog) : "memory");
                }
                if (k == NTILE - 4) mbar_arrive(bar_near);
            } else {
                const int u = k - NTILE;
                if (++slot == NSLOT) { slot = 0; ph ^= 1; }
                mbar_wait(bar_empty + 8 * slot, ph);
                if (u == 0) win = (RANK_T >> ((min(max(FB_TOTAL - 1 - total, 0), NATT - 1) >> 4) * 4)) & 15;
                mbar_expect(bar_w + 8 * u, WO_BOX);
                if (u < 5)
                    tensor_load(sbase + u * WO_BOX, u < 2 ? &map_wo : &map_w1, u < 2 ? qq * 144 + u * 72 : cta * 48,
                                u < 2 ? head * 128 : (u - 2) * 192, bar_w + 8 * u);
                else tensor_load3(sbase + u * WO_BOX, &map_w2, cta * 48 + (u - 5) * 16, bar_w + 8 * u);
            }
        }
        return;
    }

    uint32_t epoch = ld_rlx1(S->epoch);
    uint32_t x0 = 0, x1 = 0, c0 = 0, c1 = 0;
    if (warp < 9) {
        x0 = ldg32(x + 2 * tid);
        x1 = ldg32(x + D_MODEL + 2 * tid);
        if (is_own) { c0 = ldg32(cnd + 2 * tid); c1 = ldg32(cnd + D_MODEL + 2 * tid); }
    }
    if (lane == 0) {
#pragma unroll 1
        for (int i = warp; i < NBAR - 2; i += 10) mbar_init(bar_full + 8 * i, (i >= NSLOT && i < 2 * NSLOT) ? 4 : (i == 2 * NSLOT + 8 ? 6 : 1));
        asm volatile("fence.mbarrier_init.release.cluster;" ::: "memory");
    }
    __syncwarp();
    bar_sync<1, NTHR>();
    asm volatile("" : "+r"(epoch), "+r"(x0), "+r"(x1), "+r"(c0), "+r"(c1));
    epoch += 1;
    const uint32_t tag = epoch & 3u;

    if (warp == 9) {
        if (is_att) {
            uint4 v[1];
            poll4<1>(v, S->q + bat * (NHEAD * DHEAD) + head * DHEAD + lane * 4, 0, tag);
            *reinterpret_cast<uint2*>(smem + SM_Q + lane * 8) =
                make_uint2(__byte_perm(v[0].x, v[0].y, 0x7632), __byte_perm(v[0].z, v[0].w, 0x7632));
            __syncwarp();
            bar_arrive<5, 288>();
        }
        const int ocol = own * 16 + (lane & 7) + 8 * (lane >> 4), ob = (lane >> 3) & 1;
        float ga1 = 0.f, gb1 = 0.f, xo = 0.f;
        if (is_own) {
            int it = 0;
            while (true) {
                const uint32_t wa = ld_rlx1(S->mod + (2 * D_MODEL + ocol) * 2 + ob), wb = ld_rlx1(S->mod + (5 * D_MODEL + ocol) * 2 + ob);
                ga1 = dec(wa);
                gb1 = dec(wb);
                if (__all_sync(0xffffffffu, (((wa ^ tag) | (wb ^ tag)) & 3u) == 0)) break;
                if (++it > SPIN_LIMIT) __trap();
                __nanosleep(2000);
            }
            const uint32_t xw = ldg32(x + ob * D_MODEL + (ocol & ~1));
            xo = (ocol & 1) ? bfhi(xw) : bflo(xw);
        } else {
#pragma unroll 1
            for (int r = 0; r < 9; r++) {
                uint4 sb, cb;
                int it = 0;
                while (true) {
                    sb = ld_rlx4(S->mod + (3 * D_MODEL + 2 * (lane + 32 * r)) * 2);
                    cb = ld_rlx4(S->mod + (4 * D_MODEL + 2 * (lane + 32 * r)) * 2);
                    if (__all_sync(0xffffffffu, ((bad4(sb, tag) | bad4(cb, tag)) & 3u) == 0)) break;
                    if (++it > SPIN_LIMIT) __trap();
                    __nanosleep(2000);
                }
                unsigned char* p = smem + SM_XPC + r * XP_WARP + (c4 * 8 + g) * 4;
                *reinterpret_cast<uint32_t*>(p) = pack_bf(1.0f + dec(cb.x), 1.0f + dec(cb.z));
                *reinterpret_cast<uint32_t*>(p + XP_COL) = pack_bf(1.0f + dec(cb.y), 1.0f + dec(cb.w));
                *reinterpret_cast<uint32_t*>(p + 2 * XP_COL) = __byte_perm(sb.x, sb.z, 0x7632);
                *reinterpret_cast<uint32_t*>(p + 3 * XP_COL) = __byte_perm(sb.y, sb.w, 0x7632);
            }
        }
        if (is_att) {
            mbar_wait(bar_near, 0);
            const uint32_t* pp = S->part + head * 4 * PART_STRIDE;
            uint2 t;
            int it = 0;
            while (true) {
                t = ld_rlx2(pp + c4 * PART_STRIDE + 128);
                if (__all_sync(0xffffffffu, (((t.x ^ tag) | (t.y ^ tag)) & 3u) == 0)) break;
                if (++it > SPIN_LIMIT) __trap();
            }
            const float mo = __shfl_xor_sync(0xffffffffu, dec(t.x), 1);
            float e = ex2(dec(t.x) - fmaxf(dec(t.x), mo));
            const float le = e * dec(t.y);
            e *= rcp(le + __shfl_xor_sync(0xffffffffu, le, 1));
            const float e0 = __shfl_sync(0xffffffffu, e, 0), e1 = __shfl_sync(0xffffffffu, e, 1);
            const float e2 = __shfl_sync(0xffffffffu, e, 2), e3 = __shfl_sync(0xffffffffu, e, 3);
            uint4 u[4];
            poll4<4>(u, pp + 4 * lane, PART_STRIDE, tag);
            uint32_t* so = reinterpret_cast<uint32_t*>(smem + SM_O) + (c4 & 1) * 40 + g * 2 + (c4 >> 1);
            so[0] = pack_bf(fmaf(e0, dec(u[0].x), e1 * dec(u[1].x)), fmaf(e0, dec(u[0].y), e1 * dec(u[1].y)));
            so[20] = pack_bf(fmaf(e0, dec(u[0].z), e1 * dec(u[1].z)), fmaf(e0, dec(u[0].w), e1 * dec(u[1].w)));
            so[80] = pack_bf(fmaf(e2, dec(u[2].x), e3 * dec(u[3].x)), fmaf(e2, dec(u[2].y), e3 * dec(u[3].y)));
            so[100] = pack_bf(fmaf(e2, dec(u[2].z), e3 * dec(u[3].z)), fmaf(e2, dec(u[2].w), e3 * dec(u[3].w)));
            __syncwarp();
            bar_arrive<6, 320>();
        }
        if (is_own) {
            uint4 v[8];
            poll4<8>(v, S->y + (own * NHEAD + (lane >> 3)) * 32 + 4 * (lane & 7), 128, tag);
            float s[4];
            s[0] = ((dec(v[0].x) + dec(v[1].x)) + (dec(v[2].x) + dec(v[3].x))) + ((dec(v[4].x) + dec(v[5].x)) + (dec(v[6].x) + dec(v[7].x)));
            s[1] = ((dec(v[0].y) + dec(v[1].y)) + (dec(v[2].y) + dec(v[3].y))) + ((dec(v[4].y) + dec(v[5].y)) + (dec(v[6].y) + dec(v[7].y)));
            s[2] = ((dec(v[0].z) + dec(v[1].z)) + (dec(v[2].z) + dec(v[3].z))) + ((dec(v[4].z) + dec(v[5].z)) + (dec(v[6].z) + dec(v[7].z)));
            s[3] = ((dec(v[0].w) + dec(v[1].w)) + (dec(v[2].w) + dec(v[3].w))) + ((dec(v[4].w) + dec(v[5].w)) + (dec(v[6].w) + dec(v[7].w)));
            const bool b4 = lane & 16, b3 = lane & 8;
            const float t0 = (b4 ? s[2] : s[0]) + __shfl_xor_sync(0xffffffffu, b4 ? s[0] : s[2], 16);
            const float t1 = (b4 ? s[3] : s[1]) + __shfl_xor_sync(0xffffffffu, b4 ? s[1] : s[3], 16);
            const float att = (b3 ? t1 : t0) + __shfl_xor_sync(0xffffffffu, b3 ? t0 : t1, 8);
            const float x2v = rbf(xo + rbf(ga1 * rbf(att)));
            st_rlx1(S->x2 + ocol * 2 + ob, enc(x2v, tag));
            bar_arrive<4, 288>();
            bar_sync<7, 288>();
            const float* p = s_red + lane;
            const float z = ((p[0] + p[32]) + (p[64] + p[96])) + ((p[128] + p[160]) + (p[192] + p[224]));
            out[ob * D_MODEL + ocol] = __float2bfloat16_rn(x2v + rbf(gb1 * rbf(z)));
        }
        return;
    }

    const int r0 = 2 * tid;
    const uint32_t xp_st = warp * XP_WARP + (c4 * 8 + g) * 4;
    const uint32_t xp_ld = warp * XP_WARP + (g & 3) * XP_COL + c4 * 32;
    uint4 f0, f1;
    if (is_own) {
        *reinterpret_cast<uint32_t*>(smem + SM_XPD + xp_st) = pack_bf(silu_bf(bflo(c0)), silu_bf(bfhi(c0)));
        *reinterpret_cast<uint32_t*>(smem + SM_XPD + XP_COL + xp_st) = pack_bf(silu_bf(bflo(c1)), silu_bf(bfhi(c1)));
        __syncwarp();
        f0 = *reinterpret_cast<const uint4*>(smem + SM_XPD + xp_ld - (g & 2) * XP_COL);
        f1 = *reinterpret_cast<const uint4*>(smem + SM_XPD + xp_ld - (g & 2) * XP_COL + 16);
    }
    ln_partial(bflo(x0), bfhi(x0), bflo(x1), bfhi(x1), s_ml, warp, lane);
    bar_sync<3, NWORK>();
    if (is_own) {
        const int nunit = is_att ? 1 : 19;
#pragma unroll 1
        for (int u = 0; u < nunit; u++) {
            mbar_wait(bar_pm, u & 1);
            float* red = s_red + (u & 1) * 576;
            gemv32(sbase + (warp < 3 ? SM_PM0 : (warp / 3 - 1) * P_BOX), f0, f1, red, warp, lane);
            bar_sync<3, NWORK>();
            if (tid == 64) mbar_arrive(bar_fm);
            if (tid < 64) st_rlx1(S->mod + (u == 0 ? own : (2 + cta - NATT) * 18 + u - 1) * 64 + tid, enc(rbf(sum9(red + tid, 64)), tag));
        }
    }
    if (is_att) {
        float m0, rs0, m1, rs1;
        ln_stats(s_ml, m0, rs0, m1, rs1);
        const float n00 = rbf(rbf(bflo(x0) - m0) * rs0), n01 = rbf(rbf(bfhi(x0) - m0) * rs0);
        const float n10 = rbf(rbf(bflo(x1) - m1) * rs1), n11 = rbf(rbf(bfhi(x1) - m1) * rs1);
        uint4 v[2];
        poll4<2>(v, S->mod + 2 * r0, 2 * D_MODEL, tag);
        *reinterpret_cast<uint32_t*>(smem + SM_XPD + xp_st) =
            pack_bf(rbf(n00 * rbf(1.0f + dec(v[1].x))) + dec(v[0].x), rbf(n01 * rbf(1.0f + dec(v[1].z))) + dec(v[0].z));
        *reinterpret_cast<uint32_t*>(smem + SM_XPD + XP_COL + xp_st) =
            pack_bf(rbf(n10 * rbf(1.0f + dec(v[1].y))) + dec(v[0].y), rbf(n11 * rbf(1.0f + dec(v[1].w))) + dec(v[0].w));
        __syncwarp();
        f0 = *reinterpret_cast<const uint4*>(smem + SM_XPD + xp_ld - (g & 2) * XP_COL);
        f1 = *reinterpret_cast<const uint4*>(smem + SM_XPD + xp_ld - (g & 2) * XP_COL + 16);
        mbar_wait(bar_pq, 0);
        gemv32(sbase + SM_PQ + (warp / 3) * P_BOX, f0, f1, s_red + 576, warp, lane);
        bar_sync<3, NWORK>();
        if (tid == 64) mbar_arrive(bar_fq);
        if (tid < 64)
            st_rlx1(S->q + (tid >> 5) * (NHEAD * DHEAD) + cta * 32 + lane, enc(rbf(sum9(s_red + 576 + lane * 2 + (tid >> 5), 64)), tag));
        if (warp < 8) bar_sync<5, 288>();
    }

    if (is_att && warp < 8) {
        uint32_t qf[8][2], msk[8];
        const int jj = g ^ (2 * c4);
#pragma unroll
        for (int j = 0; j < 8; j++) {
            qf[j][0] = *reinterpret_cast<const uint32_t*>(smem + SM_Q + (8 * (g ^ j) + 2 * c4) * 2);
            qf[j][1] = *reinterpret_cast<const uint32_t*>(smem + SM_Q + (64 + 8 * (g ^ j) + 2 * c4) * 2);
            msk[j] = (j == jj) ? 0x0000ffffu : ((j == (jj ^ 1)) ? 0xffff0000u : 0u);
        }
        const int wq4 = warp & 3;
        const uint32_t koff = sbase + SM_RING + (wq4 * 16 + (lane & 7) + ((lane >> 3) & 1) * 8) * 256 + (lane >> 4) * 128 + (lane & 7) * 16;
        const uint32_t voff = sbase + SM_RING + (wq4 * 16 + (lane & 7) + (lane >> 4) * 8) * 256 + ((lane >> 3) & 1) * 128 + (lane & 7) * 16;
        const bool useful = (c4 == (g >> 1));
        const float SCALE = 0.08838834764831845f, LOG2E = 1.4426950408889634f;
        float m_run = -INFINITY, l_run = 0.f, esc = 0.f;
        float oa[4] = {0.f, 0.f, 0.f, 0.f}, ob[4] = {0.f, 0.f, 0.f, 0.f};
        int slot = (warp >> 2) * 2;
        uint32_t ph = 0;
#pragma unroll 1
        for (int it = 0; it < NPAIR / 2; it++) {
            mbar_wait(bar_full + 8 * slot, ph);
            float sa[4] = {0.f, 0.f, 0.f, 0.f}, sb[4] = {0.f, 0.f, 0.f, 0.f};
            const uint32_t ka = koff + ring_pos(slot);
#pragma unroll
            for (int j = 0; j < 8; j++) {
                uint32_t a[4];
                ldsm4(a, ka ^ (j << 4));
                if (j & 1) mma16816(sb, a, qf[j][0], qf[j][1]);
                else mma16816(sa, a, qf[j][0], qf[j][1]);
            }
            __syncwarp();
            if (lane == 0) mbar_arrive(bar_empty + 8 * slot);
            float slo = (g & 1) ? sa[1] + sb[1] : sa[0] + sb[0];
            float shi = (g & 1) ? sa[3] + sb[3] : sa[2] + sb[2];
            slo = useful ? rbf(rbf(slo) * SCALE) * LOG2E : -INFINITY;
            shi = useful ? rbf(rbf(shi) * SCALE) * LOG2E : -INFINITY;
            float mx = fmaxf(slo, shi);
            if (__any_sync(0xffffffffu, mx > m_run)) {
#pragma unroll
                for (int o = 16; o; o >>= 1) mx = fmaxf(mx, __shfl_xor_sync(0xffffffffu, mx, o));
                const float alpha = ex2(m_run - mx);
                m_run = mx;
                l_run *= alpha;
#pragma unroll
                for (int i = 0; i < 4; i++) { oa[i] *= alpha; ob[i] *= alpha; }
            }
            const float plo = ex2(slo - m_run), phi = ex2(shi - m_run);
            l_run += plo + phi;
            const uint32_t pk = pack_bf(plo, phi);
            const uint32_t pa = __shfl_sync(0xffffffffu, pk, 9 * c4), pb = __shfl_sync(0xffffffffu, pk, 9 * c4 + 4);
            const uint32_t p0 = __byte_perm(pa, pb, 0x5410), p1 = __byte_perm(pa, pb, 0x7632);
            if (it == NPAIR / 2 - 1) {
#pragma unroll
                for (int o = 16; o; o >>= 1) l_run += __shfl_xor_sync(0xffffffffu, l_run, o);
                if (lane == 0) *reinterpret_cast<float2*>(s_ml + 2 * warp) = make_float2(m_run, l_run);
                bar_sync<2, 256>();
                const float2 w = *reinterpret_cast<const float2*>(s_ml + 2 * (lane & 7));
                float M = w.x;
#pragma unroll
                for (int o = 4; o; o >>= 1) M = fmaxf(M, __shfl_xor_sync(0xffffffffu, M, o));
                esc = ex2(m_run - M);
                if (warp == 0) {
                    float L = w.y * ex2(w.x - M);
#pragma unroll
                    for (int o = 4; o; o >>= 1) L += __shfl_xor_sync(0xffffffffu, L, o);
                    if (lane < 8) st_rlx1(S->part + cta * PART_STRIDE + 128 + lane, enc(lane == 0 ? M : L, tag));
                }
            }
            if (++slot == NSLOT) { slot = 0; ph ^= 1; }
            mbar_wait(bar_full + 8 * slot, ph);
            const uint32_t va = voff + ring_pos(slot);
#pragma unroll
            for (int j = 0; j < 8; j++) {
                uint32_t a[4];
                ldsm4t(a, va ^ (j << 4));
                if (j & 1) mma16816(ob, a, p0 & msk[j], p1 & msk[j]);
                else mma16816(oa, a, p0 & msk[j], p1 & msk[j]);
            }
            __syncwarp();
            if (lane == 0) mbar_arrive(bar_empty + 8 * slot);
            slot += 3;
            if (slot >= NSLOT) { slot -= NSLOT; ph ^= 1; }
        }
        s_red[warp * 128 + 16 * c4 + g] = (oa[0] + ob[0]) * esc;
        s_red[warp * 128 + 16 * c4 + 8 + g] = (oa[1] + ob[1]) * esc;
        s_red[warp * 128 + 64 + 16 * c4 + g] = (oa[2] + ob[2]) * esc;
        s_red[warp * 128 + 64 + 16 * c4 + 8 + g] = (oa[3] + ob[3]) * esc;
        bar_sync<2, 256>();
        if (tid < 128) {
            const float* p = s_red + tid;
            st_rlx1(S->part + cta * PART_STRIDE + tid,
                    enc(((p[0] + p[128]) + (p[256] + p[384])) + ((p[512] + p[640]) + (p[768] + p[896])), tag));
        }
    }

    if (is_att) {
        const int G = 2 * warp + ((lane >> 3) & 1);
        const uint32_t wa = sbase + SM_WO + (G >= 9 ? WO_BOX + (G - 9) * 16 : G * 16) + ((lane & 7) + (lane >> 4) * 8) * 144;
        uint32_t wf[8][4];
        mbar_wait(bar_w, 0);
        mbar_wait(bar_w + 8, 0);
#pragma unroll
        for (int s = 0; s < 8; s++) ldsm4t(wf[s], wa + s * 16 * 144);
        bar_sync<6, 320>();
        float d[4][4];
        const uint4* p = reinterpret_cast<const uint4*>(smem + SM_O + (g & 1) * 320 + c4 * 80);
#pragma unroll
        for (int i = 0; i < 4; i++) {
            const uint4 v = p[i];
            d[i][0] = d[i][1] = d[i][2] = d[i][3] = 0.f;
            mma16816(d[i], wf[2 * i], v.x, v.y);
            mma16816(d[i], wf[2 * i + 1], v.z, v.w);
        }
        if (c4 == 0) {
            const float y0 = (d[0][0] + d[1][0]) + (d[2][0] + d[3][0]), y1 = (d[0][1] + d[1][1]) + (d[2][1] + d[3][1]);
            const float y2 = (d[0][2] + d[1][2]) + (d[2][2] + d[3][2]), y3 = (d[0][3] + d[1][3]) + (d[2][3] + d[3][3]);
            st_rlx4(S->y + ((9 * qq + warp) * NHEAD + head) * 32 + 4 * g, enc(y0, tag), enc(y1, tag), enc(y2, tag), enc(y3, tag));
        }
    }
    if (is_own) {
        if (warp < 8) {
            bar_sync<4, 288>();
            uint4 v[3];
            poll4<3>(v, S->z + (own * NMLP + warp * 12 + (lane >> 3)) * 32 + 4 * (lane & 7), 128, tag);
            float s[4];
            s[0] = dec(v[0].x) + dec(v[1].x) + dec(v[2].x);
            s[1] = dec(v[0].y) + dec(v[1].y) + dec(v[2].y);
            s[2] = dec(v[0].z) + dec(v[1].z) + dec(v[2].z);
            s[3] = dec(v[0].w) + dec(v[1].w) + dec(v[2].w);
            const bool b4 = lane & 16, b3 = lane & 8;
            const float t0 = (b4 ? s[2] : s[0]) + __shfl_xor_sync(0xffffffffu, b4 ? s[0] : s[2], 16);
            const float t1 = (b4 ? s[3] : s[1]) + __shfl_xor_sync(0xffffffffu, b4 ? s[1] : s[3], 16);
            s_red[warp * 32 + lane] = (b3 ? t1 : t0) + __shfl_xor_sync(0xffffffffu, b3 ? t0 : t1, 8);
            __syncwarp();
            bar_arrive<7, 288>();
        }
    } else {
        uint32_t w1f[12][4], w2f[12][4];
        const uint32_t w1a = sbase + SM_W1 + (warp * 64 + (lane & 7) + (lane >> 4) * 8) * 96 + ((lane >> 3) & 1) * 16;
        const uint32_t w2a = sbase + SM_W2 + warp * 2048 + ((lane & 7) + (lane >> 4) * 8) * 128 + ((((lane >> 3) & 1) ^ (lane & 7)) << 4);
        const uint32_t ca = *reinterpret_cast<const uint32_t*>(smem + SM_XPC + xp_st);
        const uint32_t cb = *reinterpret_cast<const uint32_t*>(smem + SM_XPC + XP_COL + xp_st);
        bool w2_early[3] = {false, false, false};
#pragma unroll
        for (int i = 0; i < 12; i++) w2f[i][0] = w2f[i][1] = w2f[i][2] = w2f[i][3] = 0;
        uint4 v[1];
        mbar_wait(bar_w + 8 * (2 + warp / 3), 0);
        v[0] = ld_rlx4(S->x2 + 4 * tid);
#pragma unroll
        for (int i = 0; i < 12; i++) ldsm4t(w1f[i], w1a + (i / 3) * 16 * 96 + (i % 3) * 32);
        if (!__all_sync(0xffffffffu, (bad4(v[0], tag) & 3u) == 0)) {
#pragma unroll
            for (int s = 0; s < 3; s++) {
                w2_early[s] = __all_sync(0xffffffffu, mbar_test(bar_w + 8 * (5 + s), 0));
                if (w2_early[s]) {
#pragma unroll
                    for (int t = 0; t < 4; t++) ldsm4t(w2f[3 * t + s], (w2a + s * W2_BOX) ^ (t << 5));
                }
            }
            poll4<1>(v, S->x2 + 4 * tid, 0, tag);
        }
        if (tid == 0) mbar_arrive(bar_x2);
        const float a0 = dec(v[0].x), b0 = dec(v[0].y), a1 = dec(v[0].z), b1 = dec(v[0].w);
        {
            const float pa0 = a0 * bflo(ca), pa1 = a1 * bfhi(ca), pb0 = b0 * bflo(cb), pb1 = b1 * bfhi(cb);
            const uint32_t ha = pack_bf(pa0, pa1), hb = pack_bf(pb0, pb1);
            unsigned char* p = smem + SM_XPD + xp_st;
            *reinterpret_cast<uint32_t*>(p) = ha;
            *reinterpret_cast<uint32_t*>(p + XP_COL) = hb;
            *reinterpret_cast<uint32_t*>(p + 2 * XP_COL) = pack_bf(pa0 - bflo(ha), pa1 - bfhi(ha));
            *reinterpret_cast<uint32_t*>(p + 3 * XP_COL) = pack_bf(pb0 - bflo(hb), pb1 - bfhi(hb));
        }
        __syncwarp();
        const unsigned char* fp = smem + (g < 4 ? SM_XPD : SM_XPC) + xp_ld;
        f0 = *reinterpret_cast<const uint4*>(fp);
        f1 = *reinterpret_cast<const uint4*>(fp + 16);
        const bool odd = lane & 1;
        const float sa = a0 + a1, qa = fmaf(a0, a0, a1 * a1), sb = b0 + b1, qb = fmaf(b0, b0, b1 * b1);
        float ls = (odd ? sb : sa) + __shfl_xor_sync(0xffffffffu, odd ? sa : sb, 1);
        float lq = (odd ? qb : qa) + __shfl_xor_sync(0xffffffffu, odd ? qa : qb, 1);
        const uint32_t bf[8] = {f0.x, f0.y, f0.z, f0.w, f1.x, f1.y, f1.z, f1.w};
        float d1[3][4];
#pragma unroll
        for (int t = 0; t < 3; t++) d1[t][0] = d1[t][1] = d1[t][2] = d1[t][3] = 0.f;
#pragma unroll
        for (int s = 0; s < 4; s++) {
            const float ts = __shfl_xor_sync(0xffffffffu, ls, 2 << s), tq = __shfl_xor_sync(0xffffffffu, lq, 2 << s);
#pragma unroll
            for (int t = 0; t < 3; t++) mma16816(d1[t], w1f[3 * s + t], bf[2 * s], bf[2 * s + 1]);
            ls += ts;
            lq += tq;
        }
        if (lane < 2) *reinterpret_cast<float2*>(s_ml + 4 * warp + 2 * lane) = make_float2(ls, lq);
        float* s_hp = reinterpret_cast<float*>(smem + SM_HP);
#pragma unroll
        for (int t = 0; t < 3; t++) {
            *reinterpret_cast<float2*>(s_hp + warp * 384 + t * 128 + 2 * lane) = make_float2(d1[t][0], d1[t][1]);
            *reinterpret_cast<float2*>(s_hp + warp * 384 + t * 128 + 64 + 2 * lane) = make_float2(d1[t][2], d1[t][3]);
        }
        bar_sync<3, NWORK>();
        if (warp < 6) {
            float2 t[9];
#pragma unroll
            for (int w = 0; w < 9; w++) t[w] = *reinterpret_cast<const float2*>(s_hp + w * 384 + 2 * tid);
            float m0, rs0, m1, rs1;
            ln_stats(s_ml, m0, rs0, m1, rs1);
            float u0 = ((t[0].x + t[1].x) + (t[2].x + t[3].x)) + ((t[4].x + t[5].x) + (t[6].x + t[7].x)) + t[8].x;
            float u1 = ((t[0].y + t[1].y) + (t[2].y + t[3].y)) + ((t[4].y + t[5].y) + (t[6].y + t[7].y)) + t[8].y;
            u0 *= c4 == 3 ? 1.0f : (c4 == 2 ? -rs0 * m0 : rs0);
            u1 *= c4 == 3 ? 1.0f : (c4 == 2 ? -rs1 * m1 : rs1);
            float u = (c4 & 1 ? u1 : u0) + __shfl_xor_sync(0xffffffffu, c4 & 1 ? u0 : u1, 1);
            u += __shfl_xor_sync(0xffffffffu, u, 2);
            const int k = tid >> 2, r = k & 15;
            if (c4 < 2)
                reinterpret_cast<bf16*>(smem + SM_H1)[c4 * 48 + ((r & 7) >> 1) * 12 + (k >> 4) * 4 + (r >> 3) * 2 + (r & 1)] =
                    __float2bfloat16_rn(fmaxf(u, 0.0f));
            __syncwarp();
            if (lane == 0) mbar_arrive(bar_h1);
        }
#pragma unroll
        for (int s = 0; s < 3; s++) {
            if (!w2_early[s] && __all_sync(0xffffffffu, mbar_test(bar_w + 8 * (5 + s), 0))) {
                w2_early[s] = true;
#pragma unroll
                for (int t = 0; t < 4; t++) ldsm4t(w2f[3 * t + s], (w2a + s * W2_BOX) ^ (t << 5));
            }
        }
        mbar_wait(bar_h1, 0);
        const uint2* p = reinterpret_cast<const uint2*>(smem + SM_H1 + (g & 1) * 96 + c4 * 24);
        const uint2 hf[3] = {p[0], p[1], p[2]};
        float d[4][4];
#pragma unroll
        for (int t = 0; t < 4; t++) d[t][0] = d[t][1] = d[t][2] = d[t][3] = 0.f;
#pragma unroll
        for (int s = 0; s < 3; s++) {
            if (!w2_early[s]) {
                mbar_wait(bar_w + 8 * (5 + s), 0);
#pragma unroll
                for (int t = 0; t < 4; t++) ldsm4t(w2f[3 * t + s], (w2a + s * W2_BOX) ^ (t << 5));
            }
#pragma unroll
            for (int t = 0; t < 4; t++) mma16816(d[t], w2f[3 * t + s], hf[s].x, hf[s].y);
        }
        {
            float r[4];
#pragma unroll
            for (int i = 0; i < 4; i++) r[i] = (c4 & 2) ? ((c4 & 1) ? d[3][i] : d[2][i]) : ((c4 & 1) ? d[1][i] : d[0][i]);
            st_rlx4(S->z + ((warp * 4 + c4) * NMLP + cta) * 32 + 4 * g, enc(r[0], tag), enc(r[1], tag), enc(r[2], tag), enc(r[3], tag));
        }
        if (cta == 0 && tid == 0) {
            st_rlx1(S->epoch, epoch);
            st_rlx1(S->prog + ((epoch + 1) & 1) * 32, 0);
        }
    }
}

struct PlainScratch {
    float act[2 * D_MODEL], mod[2 * NMODC], q[2 * NHEAD * DHEAD], o[2 * NHEAD * DHEAD], x2[2 * D_MODEL], h1[2 * DFF];
    float part[2 * NHEAD * 16 * 132];
};
__device__ PlainScratch g_plain;

__global__ void plain_act(int mode, const bf16* in, PlainScratch* P) {
    __shared__ float red[2][D_MODEL / 32];
    const int b = blockIdx.x, i = threadIdx.x;
    const float v = mode == 2 ? P->x2[b * D_MODEL + i] : __bfloat162float(in[b * D_MODEL + i]);
    if (mode == 0) { P->act[b * D_MODEL + i] = rbf(silu_bf(v)); return; }
    float s = v, q = v * v;
    for (int o = 16; o; o >>= 1) { s += __shfl_xor_sync(0xffffffffu, s, o); q += __shfl_xor_sync(0xffffffffu, q, o); }
    if ((i & 31) == 0) { red[0][i >> 5] = s; red[1][i >> 5] = q; }
    __syncthreads();
    s = q = 0.f;
    for (int w = 0; w < D_MODEL / 32; w++) { s += red[0][w]; q += red[1][w]; }
    const float m = s / D_MODEL, den = rbf(sqrtf(rbf(rbf(fmaxf(q / D_MODEL - m * m, 0.f)) + 1e-5f)));
    const float* mod = P->mod + b * NMODC + (mode == 1 ? 0 : 3 * D_MODEL);
    P->act[b * D_MODEL + i] = rbf(rbf(rbf(rbf(v - rbf(m)) / den) * rbf(1.0f + mod[D_MODEL + i])) + mod[i]);
}
__global__ void plain_gemv(int mode, const float* a, const bf16* W, int K, int N, float* y, const bf16* x, bf16* out, PlainScratch* P) {
    const int n = blockIdx.x * 32 + threadIdx.x, b = blockIdx.y;
    __shared__ float red[8][32];
    float s = 0.f;
    for (int k = threadIdx.y; k < K; k += 8) s = fmaf(a[b * K + k], __bfloat162float(W[(size_t)k * N + n]), s);
    red[threadIdx.y][threadIdx.x] = s;
    __syncthreads();
    if (threadIdx.y) return;
    for (int w = 1; w < 8; w++) s += red[w][threadIdx.x];
    s = rbf(s);
    if (mode == 2) P->x2[b * N + n] = rbf(__bfloat162float(x[b * N + n]) + rbf(P->mod[b * NMODC + 2 * D_MODEL + n] * s));
    else if (mode == 3) out[b * N + n] = __float2bfloat16_rn(P->x2[b * N + n] + rbf(P->mod[b * NMODC + 5 * D_MODEL + n] * s));
    else y[b * N + n] = mode == 1 ? fmaxf(s, 0.f) : s;
}
__global__ void plain_attn(const bf16* kc, const bf16* vc, PlainScratch* P) {
    const int p = blockIdx.x, sp = blockIdx.y, lane = threadIdx.x;
    const float4 q = *reinterpret_cast<const float4*>(P->q + p * DHEAD + 4 * lane);
    float m = -INFINITY, l = 0.f, o[4] = {0.f, 0.f, 0.f, 0.f};
    for (int k = sp * (SKV / 16); k < (sp + 1) * (SKV / 16); k++) {
        const uint2 kk = *reinterpret_cast<const uint2*>(kc + ((size_t)p * SKV + k) * DHEAD + 4 * lane);
        const uint2 vv = *reinterpret_cast<const uint2*>(vc + ((size_t)p * SKV + k) * DHEAD + 4 * lane);
        float s = q.x * bflo(kk.x) + q.y * bfhi(kk.x) + q.z * bflo(kk.y) + q.w * bfhi(kk.y);
        for (int w = 16; w; w >>= 1) s += __shfl_xor_sync(0xffffffffu, s, w);
        s = rbf(rbf(s) * 0.08838834764831845f);
        const float mn = fmaxf(m, s), al = __expf(m - mn), e = __expf(s - mn);
        m = mn;
        l = l * al + e;
        o[0] = o[0] * al + e * bflo(vv.x); o[1] = o[1] * al + e * bfhi(vv.x);
        o[2] = o[2] * al + e * bflo(vv.y); o[3] = o[3] * al + e * bfhi(vv.y);
    }
    float* dst = P->part + (p * 16 + sp) * 132;
    for (int i = 0; i < 4; i++) dst[4 * lane + i] = o[i];
    if (lane == 0) { dst[128] = m; dst[129] = l; }
}
__global__ void plain_combine(PlainScratch* P) {
    const float* src = P->part + blockIdx.x * 16 * 132;
    float M = -INFINITY, L = 0.f, o = 0.f;
    for (int i = 0; i < 16; i++) M = fmaxf(M, src[i * 132 + 128]);
    for (int i = 0; i < 16; i++) {
        const float e = __expf(src[i * 132 + 128] - M);
        L += e * src[i * 132 + 129];
        o += e * src[i * 132 + threadIdx.x];
    }
    P->o[blockIdx.x * DHEAD + threadIdx.x] = rbf(o / L);
}
void launch_plain(void* const* d_in, void* d_out, PlainScratch* P) {
    const bf16* x = (const bf16*)d_in[0];
    const dim3 tb(32, 8);
    plain_act<<<2, D_MODEL>>>(0, (const bf16*)d_in[8], P);
    plain_gemv<<<dim3(NMODC / 32, 2), tb>>>(0, P->act, (const bf16*)d_in[9], D_MODEL, NMODC, P->mod, x, nullptr, P);
    plain_act<<<2, D_MODEL>>>(1, x, P);
    plain_gemv<<<dim3(NHEAD * DHEAD / 32, 2), tb>>>(0, P->act, (const bf16*)d_in[3], D_MODEL, NHEAD * DHEAD, P->q, x, nullptr, P);
    plain_attn<<<dim3(2 * NHEAD, 16), 32>>>((const bf16*)d_in[1], (const bf16*)d_in[2], P);
    plain_combine<<<2 * NHEAD, DHEAD>>>(P);
    plain_gemv<<<dim3(D_MODEL / 32, 2), tb>>>(2, P->o, (const bf16*)d_in[4], NHEAD * DHEAD, D_MODEL, nullptr, x, nullptr, P);
    plain_act<<<2, D_MODEL>>>(2, x, P);
    plain_gemv<<<dim3(DFF / 32, 2), tb>>>(1, P->act, (const bf16*)d_in[6], D_MODEL, DFF, P->h1, x, nullptr, P);
    plain_gemv<<<dim3(D_MODEL / 32, 2), tb>>>(3, P->h1, (const bf16*)d_in[7], DFF, D_MODEL, nullptr, x, (bf16*)d_out, P);
}

typedef CUresult (*EncodeFn)(CUtensorMap*, CUtensorMapDataType, cuuint32_t, void*, const cuuint64_t*, const cuuint64_t*,
                             const cuuint32_t*, const cuuint32_t*, CUtensorMapInterleave, CUtensorMapSwizzle,
                             CUtensorMapL2promotion, CUtensorMapFloatOOBfill);

void make_map(EncodeFn fn, CUtensorMap* m, const void* p, uint64_t cols, uint64_t rows, uint32_t bcols, uint32_t brows,
              CUtensorMapSwizzle swz) {
    const cuuint64_t dims[2] = {cols, rows};
    const cuuint64_t strides[1] = {cols * 2};
    const cuuint32_t box[2] = {bcols, brows};
    const cuuint32_t es[2] = {1, 1};
    fn(m, CU_TENSOR_MAP_DATA_TYPE_BFLOAT16, 2, const_cast<void*>(p), dims, strides, box, es, CU_TENSOR_MAP_INTERLEAVE_NONE,
       swz, CU_TENSOR_MAP_L2_PROMOTION_L2_128B, CU_TENSOR_MAP_FLOAT_OOB_FILL_NONE);
}

}

extern "C" void kernel_launch(void* const* d_in, const int* in_sizes, int n_in, void* d_out, int out_size) {
    (void)in_sizes; (void)n_in; (void)out_size;
    static bool init = false, fits = false;
    static EncodeFn encode = nullptr;
    static Scratch* scratch = nullptr;
    static PlainScratch* plain = nullptr;
    if (!init) {
        init = true;
        cudaGetSymbolAddress(reinterpret_cast<void**>(&scratch), g_scratch);
        cudaGetSymbolAddress(reinterpret_cast<void**>(&plain), g_plain);
        void* fn = nullptr;
        cudaDriverEntryPointQueryResult st;
        cudaGetDriverEntryPoint("cuTensorMapEncodeTiled", &fn, cudaEnableDefault, &st);
        encode = reinterpret_cast<EncodeFn>(fn);
        int dev = 0, sms = 0, per_sm = 0;
        cudaGetDevice(&dev);
        cudaDeviceGetAttribute(&sms, cudaDevAttrMultiProcessorCount, dev);
        cudaFuncSetAttribute(adaln_block_kernel, cudaFuncAttributeMaxDynamicSharedMemorySize, SM_TOTAL);
        cudaOccupancyMaxActiveBlocksPerMultiprocessor(&per_sm, adaln_block_kernel, NTHR, SM_TOTAL);
        fits = encode && sms * per_sm >= NCTA;
    }
    if (!fits) { launch_plain(d_in, d_out, plain); return; }
    CUtensorMap mwm, mwq, mwo, mw1, mw2;
    make_map(encode, &mwm, d_in[9], NMODC, D_MODEL, 32, 192, CU_TENSOR_MAP_SWIZZLE_64B);
    make_map(encode, &mwq, d_in[3], NHEAD * DHEAD, D_MODEL, 32, 192, CU_TENSOR_MAP_SWIZZLE_64B);
    make_map(encode, &mwo, d_in[4], D_MODEL, NHEAD * DHEAD, 72, 128, CU_TENSOR_MAP_SWIZZLE_NONE);
    make_map(encode, &mw1, d_in[6], DFF, D_MODEL, 48, 192, CU_TENSOR_MAP_SWIZZLE_NONE);
    {
        const cuuint64_t dims[3] = {64, DFF, 9};
        const cuuint64_t strides[2] = {D_MODEL * 2, 128};
        const cuuint32_t box[3] = {64, 16, 9};
        const cuuint32_t es[3] = {1, 1, 1};
        encode(&mw2, CU_TENSOR_MAP_DATA_TYPE_BFLOAT16, 3, d_in[7], dims, strides, box, es, CU_TENSOR_MAP_INTERLEAVE_NONE,
               CU_TENSOR_MAP_SWIZZLE_128B, CU_TENSOR_MAP_L2_PROMOTION_L2_128B, CU_TENSOR_MAP_FLOAT_OOB_FILL_NONE);
    }
    const void *px = d_in[0], *pk = d_in[1], *pv = d_in[2], *pc = d_in[8];
    void* args[] = {&mwm, &mwq, &mwo, &mw1, &mw2, &px, &pk, &pv, &pc, &d_out, &scratch};
    cudaLaunchCooperativeKernel(reinterpret_cast<const void*>(adaln_block_kernel), dim3(NCTA), dim3(NTHR), args, SM_TOTAL, cudaStreamPerThread);
}
```
